```python
import torch

def _softmax(x, axis=-1):
    return torch.softmax(x, dim=axis)
def _gelu(x):
    return torch.nn.functional.gelu(x, approximate="tanh")
def _silu(x):
    return torch.nn.functional.silu(x)
def _sigmoid(x):
    return torch.sigmoid(x)
def _layernorm(x, axis=-1, eps=1e-5):
    m = x.mean(dim=axis, keepdim=True)
    v = x.var(dim=axis, keepdim=True, unbiased=False)
    return (x - m) / torch.sqrt(v + eps)
def _scatter_add(tgt, idx, src, axis=0):
    return tgt.clone().index_add_(axis, idx, src)
def _segment_sum(src, seg, n):
    out = torch.zeros((n,) + src.shape[1:], dtype=src.dtype)
    return out.index_add_(0, seg, src)
def _pad(x, pw):
    flat = tuple(v for pair in reversed(pw) for v in pair)
    return torch.nn.functional.pad(x, flat)

kernel_name = 'gated_mix__gqa_block_cached__glu_gated_geglu__decode'

def setup_inputs():

    _w = (lambda a: (lambda t: t.to(torch.bfloat16) if t.is_floating_point() else t)(torch.as_tensor(a)))
    def _A_setup():
        B, Sq, D = 2, 1, 512
        Hq, Hkv, Sk, Dh = 32, 32, 16384, 128
        assert Hq % Hkv == 0, (Hq, Hkv)
        return {
            "x": _w((lambda *s: torch.randn(*s, dtype=torch.bfloat16) * 0.05)(B, Sq, D)),
            "k_cache": _w((lambda *s: torch.randn(*s, dtype=torch.bfloat16) * 3.2)(B, Hkv, Sk, Dh)),
            "v_cache": _w((lambda *s: torch.randn(*s, dtype=torch.bfloat16) * 0.05)(B, Hkv, Sk, Dh)),
            "wq": _w((lambda *s: torch.randn(*s, dtype=torch.bfloat16) * 3.2)(D, Hq * Dh) * (D ** -0.5)),
            "wo": _w((lambda *s: torch.randn(*s, dtype=torch.bfloat16) * 0.05)(Hq * Dh, D) * ((Hq * Dh) ** -0.5)),
        }
    _A_in = _A_setup()

    def _B_setup():
        B, S, Dm, Df = 2, 1, 512, 1376
        return {
            "x": _w((lambda *s: torch.randn(*s, dtype=torch.bfloat16) * 0.05)(B, S, Dm)),
            "w_gate": _w((lambda *s: torch.randn(*s, dtype=torch.bfloat16) * 0.2)(Dm, Df) * (Dm ** -0.5)),
            "w_up": _w((lambda *s: torch.randn(*s, dtype=torch.bfloat16) * 0.2)(Dm, Df) * (Dm ** -0.5)),
            "w_down": _w((lambda *s: torch.randn(*s, dtype=torch.bfloat16) * 0.2)(Df, Dm) * (Df ** -0.5)),
        }
    _B_in = _B_setup()

    return {
        "A_x": _A_in["x"],
        "A_k_cache": _A_in["k_cache"],
        "A_v_cache": _A_in["v_cache"],
        "A_wq": _A_in["wq"],
        "A_wo": _A_in["wo"],
        "B_x": _B_in["x"],
        "B_w_gate": _B_in["w_gate"],
        "B_w_up": _B_in["w_up"],
        "B_w_down": _B_in["w_down"],
        "gate_w": _w((lambda *s: torch.randn(*s, dtype=torch.bfloat16) * 0.05)(512) * 16.0),
    }

def reference(A_x, A_k_cache, A_v_cache, A_wq, A_wo, B_x, B_w_gate, B_w_up, B_w_down, gate_w):
    def _A_ref(x, k_cache, v_cache, wq, wo):
        B, Sq, D = x.shape
        Hq, Dh = 32, 128
        Hkv = k_cache.shape[1]
        rep = Hq // Hkv
        q = (lambda x, *d: x.permute(*d))((x @ wq).reshape(B, Sq, Hq, Dh), 0, 2, 1, 3)
        k = (lambda x, n, axis: torch.repeat_interleave(x, n, dim=axis))(k_cache, rep, axis=1)
        v = (lambda x, n, axis: torch.repeat_interleave(x, n, dim=axis))(v_cache, rep, axis=1)
        scores = torch.einsum("bhqd,bhkd->bhqk", q, k) * (Dh ** -0.5)
        p = _softmax(scores, axis=-1)
        o = torch.einsum("bhqk,bhkd->bhqd", p, v)
        return (lambda x, *d: x.permute(*d))(o, 0, 2, 1, 3).reshape(B, Sq, Hq * Dh) @ wo

    def _B_ref(x, w_gate, w_up, w_down):
        g = torch.einsum("bsd,df->bsf", x, w_gate)
        u = torch.einsum("bsd,df->bsf", x, w_up)
        h = _gelu(g) * u
        return torch.einsum("bsf,fd->bsd", h, w_down)

    x = A_x
    g = _sigmoid((x * gate_w).sum(-1, keepdims=True))
    a = _A_ref(x, A_k_cache, A_v_cache, A_wq, A_wo)
    b = _B_ref(x, B_w_gate, B_w_up, B_w_down)
    return g * a + (1 - g) * b
```

```cpp
#include <cuda_runtime.h>
#include <cuda_bf16.h>
#include <stdint.h>

#define NS 12
#define CAP 3
#define PSTAT 4

#define RING 8
#define CLEAR_Y 1
#define WARM 1
#define EAGER (2 * 132)
#define PTAG(bh) (((epoch % 15u) * (64 / RING) + (bh) / RING) % 15u + 1u)
static_assert(NS >= 8 && PSTAT - 1 <= CAP && CAP >= 3, "ring");
constexpr int G = 132;
constexpr int NUNITS = 64 * 512;
constexpr int NTHREADS = 448;
constexpr int DF = 1376;
constexpr int SPIN_LIMIT = 1 << 22;

constexpr int OFF_RING = 0;
constexpr int OFF_Q = NS * 16384;
constexpr int OFF_RES = OFF_Q + 16384;
constexpr int OFF_X = OFF_RES + NS * 528;
constexpr int OFF_RED = OFF_X + 4096;
constexpr int OFF_COEF = OFF_RED + 2048;
constexpr int OFF_CMB = OFF_COEF + 192;
constexpr int OFF_META = OFF_CMB + 576;
constexpr int OFF_BAR = OFF_META + NS * 8;
constexpr int OFF_N = OFF_BAR + (3 * NS + 6) * 8;
constexpr int SMEM_BYTES = OFF_N + 16;
static_assert(SMEM_BYTES <= 232448, "smem");

__device__ unsigned g_epoch;
__device__ unsigned g_ctr[2 * 32];
__device__ uint32_t g_q[2 * 4096];
__device__ uint32_t g_h[2 * DF];
__device__ uint4 g_po[RING * 4 * G * 8];
__device__ uint2 g_pml[RING * G];
__device__ uint4 g_cons[64];
__device__ uint4 g_y[128 * 128 * 2];
#define TS(i)
#define TSV(i, v)

__device__ __forceinline__ uint32_t s2u(const void* p) { return (uint32_t)__cvta_generic_to_shared(p); }
__device__ __forceinline__ void mbar_init(uint32_t b, int c) { asm volatile("mbarrier.init.shared::cta.b64 [%0], %1;" ::"r"(b), "r"(c) : "memory"); }
__device__ __forceinline__ void mbar_expect(uint32_t b, uint32_t bytes) { asm volatile("mbarrier.arrive.expect_tx.shared::cta.b64 _, [%0], %1;" ::"r"(b), "r"(bytes) : "memory"); }
__device__ __forceinline__ void mbar_arrive(uint32_t b) { asm volatile("mbarrier.arrive.shared::cta.b64 _, [%0];" ::"r"(b) : "memory"); }
__device__ __forceinline__ void mbar_wait(uint32_t b, uint32_t ph) {
    uint32_t ok;
    int it = 0;
    do {
        asm volatile("{\n.reg .pred p;\nmbarrier.try_wait.parity.shared::cta.b64 p, [%1], %2;\nselp.u32 %0, 1, 0, p;\n}" : "=r"(ok) : "r"(b), "r"(ph) : "memory");
        if (++it > SPIN_LIMIT) __trap();
    } while (!ok);
}
__device__ __forceinline__ void bulk(uint32_t dst, const void* src, uint32_t bytes, uint32_t bar, uint64_t pol) {
    asm volatile("cp.async.bulk.shared::cluster.global.mbarrier::complete_tx::bytes.L2::cache_hint [%0], [%1], %2, [%3], %4;" ::"r"(dst), "l"(src), "r"(bytes), "r"(bar), "l"(pol) : "memory");
}
__device__ __forceinline__ uint4 lds128(uint32_t a) {
    uint4 v;
    asm volatile("ld.shared.v4.u32 {%0,%1,%2,%3}, [%4];" : "=r"(v.x), "=r"(v.y), "=r"(v.z), "=r"(v.w) : "r"(a));
    return v;
}
__device__ __forceinline__ uint4 ldsm4t(uint32_t a) {
    uint4 v;
    asm volatile("ldmatrix.sync.aligned.m8n8.x4.trans.shared.b16 {%0,%1,%2,%3}, [%4];" : "=r"(v.x), "=r"(v.y), "=r"(v.z), "=r"(v.w) : "r"(a));
    return v;
}
__device__ __forceinline__ void mma(float (&c)[4], uint32_t a0, uint32_t a1, uint32_t a2, uint32_t a3, uint32_t b0, uint32_t b1) {
    asm volatile("mma.sync.aligned.m16n8k16.row.col.f32.bf16.bf16.f32 {%0,%1,%2,%3}, {%4,%5,%6,%7}, {%8,%9}, {%0,%1,%2,%3};"
                 : "+f"(c[0]), "+f"(c[1]), "+f"(c[2]), "+f"(c[3]) : "r"(a0), "r"(a1), "r"(a2), "r"(a3), "r"(b0), "r"(b1));
}
__device__ __forceinline__ uint4 ldg_nc(const void* p) {
    uint4 v;
    asm volatile("ld.global.nc.L1::no_allocate.v4.u32 {%0,%1,%2,%3}, [%4];" : "=r"(v.x), "=r"(v.y), "=r"(v.z), "=r"(v.w) : "l"(p));
    return v;
}
__device__ __forceinline__ uint4 ld_poll4(const void* p) {
    uint4 v;
    asm volatile("ld.relaxed.gpu.global.v4.u32 {%0,%1,%2,%3}, [%4];" : "=r"(v.x), "=r"(v.y), "=r"(v.z), "=r"(v.w) : "l"(p) : "memory");
    return v;
}
__device__ __forceinline__ uint2 ld_poll2(const void* p) {
    uint2 v;
    asm volatile("ld.relaxed.gpu.global.v2.u32 {%0,%1}, [%2];" : "=r"(v.x), "=r"(v.y) : "l"(p) : "memory");
    return v;
}
__device__ __forceinline__ uint32_t ld_poll1(const void* p) {
    uint32_t v;
    asm volatile("ld.relaxed.gpu.global.u32 %0, [%1];" : "=r"(v) : "l"(p) : "memory");
    return v;
}
__device__ __forceinline__ void st_pub4(void* p, uint32_t a, uint32_t b, uint32_t c, uint32_t d) {
    asm volatile("st.relaxed.gpu.global.v4.u32 [%0], {%1,%2,%3,%4};" ::"l"(p), "r"(a), "r"(b), "r"(c), "r"(d) : "memory");
}
__device__ __forceinline__ void st_pub2(void* p, uint32_t a, uint32_t b) {
    asm volatile("st.relaxed.gpu.global.v2.u32 [%0], {%1,%2};" ::"l"(p), "r"(a), "r"(b) : "memory");
}
__device__ __forceinline__ void st_pub1(void* p, uint32_t a) {
    asm volatile("st.relaxed.gpu.global.u32 [%0], %1;" ::"l"(p), "r"(a) : "memory");
}
__device__ __forceinline__ uint32_t tg(float v, uint32_t tag) { return (__float_as_uint(v) & ~15u) | tag; }
__device__ __forceinline__ float blo(uint32_t v) { return __uint_as_float(v << 16); }
__device__ __forceinline__ float bhi(uint32_t v) { return __uint_as_float(v & 0xffff0000u); }
__device__ __forceinline__ float ex2(float x) { float r; asm("ex2.approx.ftz.f32 %0, %1;" : "=f"(r) : "f"(x)); return r; }
__device__ __forceinline__ uint32_t packbf(float lo, float hi) {
    uint32_t r;
    asm("cvt.rn.bf16x2.f32 %0, %1, %2;" : "=r"(r) : "f"(hi), "f"(lo));
    return r;
}
__device__ __forceinline__ void fma8(float (&a)[8], uint4 w, float x) {
    a[0] = fmaf(blo(w.x), x, a[0]); a[1] = fmaf(bhi(w.x), x, a[1]);
    a[2] = fmaf(blo(w.y), x, a[2]); a[3] = fmaf(bhi(w.y), x, a[3]);
    a[4] = fmaf(blo(w.z), x, a[4]); a[5] = fmaf(bhi(w.z), x, a[5]);
    a[6] = fmaf(blo(w.w), x, a[6]); a[7] = fmaf(bhi(w.w), x, a[7]);
}
__device__ __forceinline__ void cbar() { asm volatile("bar.sync 1, 256;" ::: "memory"); }

__global__ void __launch_bounds__(NTHREADS, 1)
fused_decode_kernel(const __nv_bfloat16* __restrict__ x, const __nv_bfloat16* __restrict__ Kc, const __nv_bfloat16* __restrict__ Vc,
                    const __nv_bfloat16* __restrict__ wq, const __nv_bfloat16* __restrict__ wo,
                    const __nv_bfloat16* __restrict__ wg, const __nv_bfloat16* __restrict__ wu,
                    const __nv_bfloat16* __restrict__ wd, const __nv_bfloat16* __restrict__ gw,
                    __nv_bfloat16* __restrict__ out) {
    extern __shared__ __align__(1024) unsigned char smem[];
    const int tid = threadIdx.x, lane = tid & 31, warp = tid >> 5, cta = blockIdx.x;
    const uint32_t sb = s2u(smem);
    const uint32_t bFull = sb + OFF_BAR, bDone = bFull + NS * 8, bEmpty = bDone + NS * 8, bW = bEmpty + NS * 8,
                   bCb = bW + 24, bOfin = bCb + 16;
    float* xs = (float*)(smem + OFF_X);
    volatile int2* meta = (volatile int2*)(smem + OFF_META);
    const int r0 = (cta * 43) >> 2, nr = (((cta + 1) * 43) >> 2) - r0;

    uint64_t pol = 0;
    uint4 wreg[8];
    if (warp == 8) {
        if (lane == 0) {
            TS(0);
            for (int i = 0; i < 3 * NS + 6; i++) mbar_init(bFull + i * 8, 1);
            asm volatile("fence.mbarrier_init.release.cluster;" ::: "memory");
            asm volatile("createpolicy.fractional.L2::evict_first.b64 %0, 1.0;" : "=l"(pol));
#pragma unroll
            for (int s = 0; s < PSTAT - 1; s++) {
                const int u = cta + G * s;
                meta[s].x = u; meta[s].y = u + G;
                mbar_expect(bFull + s * 8, 16384);
                bulk(sb + s * 16384, Kc + (size_t)u * 4096, 8192, bFull + s * 8, pol);
                bulk(sb + s * 16384 + 8192, Vc + (size_t)u * 4096, 8192, bFull + s * 8, pol);
            }
        }
    } else if (warp < 8) {
        if (cta < 128) {
            const __nv_bfloat16* p = wq + (size_t)(tid >> 2) * 4096 + cta * 32 + (tid & 3) * 8;
#pragma unroll
            for (int i = 0; i < 8; i++) wreg[i] = ldg_nc(p + (size_t)i * 64 * 4096);
        }
        if (tid < 128) {
            uint4 v = ldg_nc(x + tid * 8);
            float4* d = (float4*)(xs + tid * 8);
            d[0] = make_float4(blo(v.x), bhi(v.x), blo(v.y), bhi(v.y));
            d[1] = make_float4(blo(v.z), bhi(v.z), blo(v.w), bhi(v.w));
        }
    }
    const unsigned epoch = ld_poll1(&g_epoch);
    const uint32_t tag = epoch % 15u + 1u;
    __syncthreads();

    if (warp == 8) {
        if (lane == 0) {
            unsigned* ctr = &g_ctr[(epoch & 1) * 32];
            if (cta == 0) g_ctr[((epoch + 1) & 1) * 32] = 0;
            int cur = cta + G * (PSTAT - 1);
            int nxt = (int)atomicAdd(ctr, 1u) + G * PSTAT;
            int seq = PSTAT - 1, st = (PSTAT - 1) % NS, cst = (PSTAT - 1 - CAP + NS) % NS;
            uint32_t eph = 1, cph = (PSTAT - 1 - CAP < 0) ? 1 : 0;
            while (cur < NUNITS) {
                const int nn = (int)atomicAdd(ctr, 1u) + G * PSTAT;
                if (cur < NUNITS - EAGER) mbar_wait(bFull + cst * 8, cph);
                mbar_wait(bEmpty + st * 8, eph);
                meta[st].x = cur; meta[st].y = nxt;
                mbar_expect(bFull + st * 8, 16384);
                bulk(sb + st * 16384, Kc + (size_t)cur * 4096, 8192, bFull + st * 8, pol);
                bulk(sb + st * 16384 + 8192, Vc + (size_t)cur * 4096, 8192, bFull + st * 8, pol);
                if (++st == NS) { st = 0; eph ^= 1; }
                if (++cst == NS) { cst = 0; cph ^= 1; }
                ++seq;
                cur = nxt; nxt = nn;
            }
            TS(1);
            *(volatile int*)(smem + OFF_N) = st;
            int st2 = st; uint32_t eph2 = eph;
            if (cta < 128) {
#pragma unroll
                for (int i = 0; i < 3; i++) {
                    if (i < CAP) {
                        mbar_wait(bFull + cst * 8, cph);
                        if (++cst == NS) { cst = 0; cph ^= 1; }
                    }
                    mbar_wait(bEmpty + st2 * 8, eph2);
                    const uint32_t bytes = i == 0 ? nr * 1024 : 16384;
                    const __nv_bfloat16* src = i == 0 ? wd + (size_t)r0 * 512 : wo + (size_t)(cta * 32 + (i - 1) * 16) * 512;
                    mbar_expect(bW + i * 8, bytes);
                    bulk(sb + st2 * 16384, src, bytes, bW + i * 8, pol);
                    if (++st2 == NS) { st2 = 0; eph2 ^= 1; }
                }
            }
            for (int i = 0; i < 8; i++) {
                mbar_wait(bEmpty + st * 8, eph);
                meta[st].x = -1;
                mbar_arrive(bFull + st * 8);
                if (++st == NS) { st = 0; eph ^= 1; }
            }
            TS(2);
        }
    } else if (warp == 9) {
        float m = -1e30f, l = 0.f, o0 = 0.f, o1 = 0.f, o2 = 0.f, o3 = 0.f;
        int st = 0; uint32_t ph = 0;
        const int myh = cta >> 2;
        uint4 cons = make_uint4(0u, 0u, 0u, 0u);
        while (true) {
            mbar_wait(bDone + st * 8, ph);
            const int u = meta[st].x, nx = meta[st].y;
            const float* res = (const float*)(smem + OFF_RES + st * 528);
            const float4 v = *(const float4*)(res + lane * 4);
            const float2 ml = *(const float2*)(res + 128);
            __syncwarp();
            if (lane == 0) mbar_arrive(bEmpty + st * 8);
            const float mn = fmaxf(m, ml.x);
            const float a = ex2(m - mn), b = ex2(ml.x - mn);
            m = mn;
            l = l * a + ml.y * b;
            o0 = o0 * a + v.x * b; o1 = o1 * a + v.y * b; o2 = o2 * a + v.z * b; o3 = o3 * a + v.w * b;
            const int nb = min(nx >> 9, 64);
            for (int bh = u >> 9; bh < nb; bh++) {
                const uint32_t ptag = PTAG(bh);
                if (bh >= RING) {
                    int it = 0;
                    while (cons.x != epoch + 1 || cons.y != epoch + 1 || cons.z != epoch + 1 || cons.w != epoch + 1) {
                        cons = ld_poll4(&g_cons[bh - RING]);
                        if (++it > SPIN_LIMIT) __trap();
                    }
                }
                if (bh == 32 && cta < 128) {
#pragma unroll
                    for (int i = 0; i < 8; i++) st_pub4(&g_y[cta * 256 + i * 32 + lane], 0u, 0u, 0u, 0u);
                    __threadfence();
                    __syncwarp();
                }
                st_pub4(&g_po[(((bh % RING) * 4 + (lane >> 3)) * G + cta) * 8 + (lane & 7)], tg(o0, ptag), tg(o1, ptag), tg(o2, ptag), tg(o3, ptag));
                if (lane == 0) {
                    st_pub2(&g_pml[(bh % RING) * G + cta], tg(m, ptag), tg(l, ptag));
                    if ((bh & 31) == myh) mbar_arrive(bCb + (bh >> 5) * 8);
                }
                if (bh + 1 >= RING && bh < 63) cons = ld_poll4(&g_cons[bh + 1 - RING]);
                m = -1e30f; l = 0.f; o0 = o1 = o2 = o3 = 0.f;
            }
            if (nb == 64) break;
            if (++st == NS) { st = 0; ph ^= 1; }
        }
        if (lane == 0) TS(3);
    } else if (warp >= 10) {
        const int cw = warp - 10;
        if (cta >= G - 43 && cw == 1) {
            const int f0 = (cta - (G - 43)) * 32;
            float ag[2][8], au[2][8];
#pragma unroll
            for (int i = 0; i < 8; i++) ag[0][i] = ag[1][i] = au[0][i] = au[1][i] = 0.f;
            const size_t off = (size_t)(lane >> 2) * DF + f0 + (lane & 3) * 8;
            for (int it = 0; it < 8; it++) {
                uint4 a[8], b[8];
#pragma unroll
                for (int i = 0; i < 8; i++) {
                    a[i] = ldg_nc(wg + off + (size_t)(it * 64 + i * 8) * DF);
                    b[i] = ldg_nc(wu + off + (size_t)(it * 64 + i * 8) * DF);
                }
#pragma unroll
                for (int i = 0; i < 8; i++) {
                    const int r = it * 64 + i * 8 + (lane >> 2);
                    const float x0 = xs[r], x1 = xs[512 + r];
                    fma8(ag[0], a[i], x0); fma8(ag[1], a[i], x1);
                    fma8(au[0], b[i], x0); fma8(au[1], b[i], x1);
                }
            }
#pragma unroll
            for (int b = 0; b < 2; b++)
#pragma unroll
                for (int i = 0; i < 8; i++) {
#pragma unroll
                    for (int s = 4; s < 32; s <<= 1) {
                        ag[b][i] += __shfl_xor_sync(~0u, ag[b][i], s);
                        au[b][i] += __shfl_xor_sync(~0u, au[b][i], s);
                    }
                }
            if (lane < 8) {
                const int b = lane >> 2;
                uint32_t hv[8];
#pragma unroll
                for (int i = 0; i < 8; i++) {
                    const float gv = b ? ag[1][i] : ag[0][i], uv = b ? au[1][i] : au[0][i];
                    const float t = tanhf(0.7978845608028654f * (gv + 0.044715f * gv * gv * gv));
                    hv[i] = tg(0.5f * gv * (1.f + t) * uv, tag);
                }
                uint32_t* d = &g_h[b * DF + f0 + (lane & 3) * 8];
                st_pub4(d, hv[0], hv[1], hv[2], hv[3]);
                st_pub4(d + 4, hv[4], hv[5], hv[6], hv[7]);
            }
        }
        if (cta < 128) {
            __nv_bfloat16* coef = (__nv_bfloat16*)(smem + OFF_COEF);
            float* cmb = (float*)(smem + OFF_CMB);
            float gate0 = 0.f, gate1 = 0.f;
            if (cw == 0) {
                const uint4 w0 = ldg_nc(gw + lane * 16), w1 = ldg_nc(gw + lane * 16 + 8);
                const uint32_t w[8] = {w0.x, w0.y, w0.z, w0.w, w1.x, w1.y, w1.z, w1.w};
#pragma unroll
                for (int i = 0; i < 8; i++) {
                    gate0 = fmaf(blo(w[i]), xs[lane * 16 + 2 * i], gate0);
                    gate0 = fmaf(bhi(w[i]), xs[lane * 16 + 2 * i + 1], gate0);
                    gate1 = fmaf(blo(w[i]), xs[512 + lane * 16 + 2 * i], gate1);
                    gate1 = fmaf(bhi(w[i]), xs[512 + lane * 16 + 2 * i + 1], gate1);
                }
#pragma unroll
                for (int k = 1; k < 32; k <<= 1) {
                    gate0 += __shfl_xor_sync(~0u, gate0, k);
                    gate1 += __shfl_xor_sync(~0u, gate1, k);
                }
                gate0 = 1.f / (1.f + __expf(-gate0));
                gate1 = 1.f / (1.f + __expf(-gate1));
            }
#pragma unroll 1
            for (int b = 0; b < 2; b++) {
                const int bh = b * 32 + (cta >> 2);
                if (b == 1 && cw == 0) {
                    const int r = lane & 15, bb = lane >> 4;
                    uint32_t hv = tag;
                    if (r < nr) {
                        int it = 0;
                        do {
                            hv = ld_poll1(&g_h[bb * DF + r0 + r]);
                            if (++it > SPIN_LIMIT) __trap();
                        } while ((hv & 15u) != tag);
                    }
                    coef[bb * 48 + r] = __float2bfloat16(r < nr ? __uint_as_float(hv) * (1.f - (bb ? gate1 : gate0)) : 0.f);
                }
                mbar_wait(bCb + b * 8, 0);
                if (tid == 320) TS(10);
                const uint4* po = &g_po[((bh % RING) * 4 + (cta & 3)) * G * 8];
                const uint2* pm = &g_pml[(bh % RING) * G];
                const uint32_t ptag = PTAG(bh);
                uint4 v[9];
                uint2 ml, mle;
                int it = 0;
                while (true) {
                    ml = ld_poll2(pm + cw * 32 + lane);
                    mle = ld_poll2(pm + 128 + cw);
#pragma unroll
                    for (int i = 0; i < 8; i++) v[i] = ld_poll4(po + cw * 256 + i * 32 + lane);
                    v[8] = ld_poll4(po + (128 + cw) * 8 + (lane & 7));
                    uint32_t bad = (v[8].x ^ ptag) | (v[8].y ^ ptag) | (v[8].z ^ ptag) | (v[8].w ^ ptag);
#pragma unroll
                    for (int i = 7; i >= 0; i--) bad |= (v[i].x ^ ptag) | (v[i].y ^ ptag) | (v[i].z ^ ptag) | (v[i].w ^ ptag);
                    bad |= (ml.x ^ ptag) | (ml.y ^ ptag) | (mle.x ^ ptag) | (mle.y ^ ptag);
                    if (!__any_sync(~0u, (bad & 15u) != 0)) break;
                    if (++it > SPIN_LIMIT) __trap();
                }
                if (tid == 320) { TS(11); TSV(12, it); }
                float M = fmaxf(__uint_as_float(ml.x), __uint_as_float(mle.x));
#pragma unroll
                for (int k = 1; k < 32; k <<= 1) M = fmaxf(M, __shfl_xor_sync(~0u, M, k));
                const float w = ex2(__uint_as_float(ml.x) - M);
                const float we = lane < 8 ? ex2(__uint_as_float(mle.x) - M) : 0.f;
                float L = w * __uint_as_float(ml.y & ~15u) + (lane == 0 ? we * __uint_as_float(mle.y & ~15u) : 0.f);
                float o0 = we * __uint_as_float(v[8].x), o1 = we * __uint_as_float(v[8].y), o2 = we * __uint_as_float(v[8].z), o3 = we * __uint_as_float(v[8].w);
#pragma unroll
                for (int i = 0; i < 8; i++) {
                    const float wi = __shfl_sync(~0u, w, 4 * i + (lane >> 3));
                    o0 = fmaf(wi, __uint_as_float(v[i].x), o0); o1 = fmaf(wi, __uint_as_float(v[i].y), o1);
                    o2 = fmaf(wi, __uint_as_float(v[i].z), o2); o3 = fmaf(wi, __uint_as_float(v[i].w), o3);
                }
#pragma unroll
                for (int k = 1; k < 32; k <<= 1) L += __shfl_xor_sync(~0u, L, k);
#pragma unroll
                for (int k = 8; k < 32; k <<= 1) {
                    o0 += __shfl_xor_sync(~0u, o0, k); o1 += __shfl_xor_sync(~0u, o1, k);
                    o2 += __shfl_xor_sync(~0u, o2, k); o3 += __shfl_xor_sync(~0u, o3, k);
                }
                if (lane < 8) *(float4*)(cmb + cw * 36 + lane * 4) = make_float4(o0, o1, o2, o3);
                if (lane == 8) *(float2*)(cmb + cw * 36 + 32) = make_float2(M, L);
                asm volatile("bar.sync 2, 128;" ::: "memory");
                if (cw == 0) {
                    const float2 a0 = *(const float2*)(cmb + 32), a1 = *(const float2*)(cmb + 68), a2 = *(const float2*)(cmb + 104), a3 = *(const float2*)(cmb + 140);
                    const float MM = fmaxf(fmaxf(a0.x, a1.x), fmaxf(a2.x, a3.x));
                    const float e0 = ex2(a0.x - MM), e1 = ex2(a1.x - MM), e2 = ex2(a2.x - MM), e3 = ex2(a3.x - MM);
                    const float LL = (e0 * a0.y + e1 * a1.y) + (e2 * a2.y + e3 * a3.y);
                    const float o = (e0 * cmb[lane] + e1 * cmb[36 + lane]) + (e2 * cmb[72 + lane] + e3 * cmb[108 + lane]);
                    coef[b * 48 + 16 + lane] = __float2bfloat16(o * __fdividef(b ? gate1 : gate0, LL));
                    __syncwarp();
                    if (lane == 0) {
                        if (b == 1) { mbar_arrive(bOfin); TS(4); }
                        st_pub1((uint32_t*)&g_cons[bh] + (cta & 3), epoch + 1);
                    }
                }
                if (b == 0) asm volatile("bar.sync 2, 128;" ::: "memory");
            }
        }
    } else {
        float* red = (float*)(smem + OFF_RED);
        if (cta < 128) {
            float a0[8], a1[8];
#pragma unroll
            for (int i = 0; i < 8; i++) a0[i] = a1[i] = 0.f;
#pragma unroll
            for (int i = 0; i < 8; i++) {
                const int r = (tid >> 2) + 64 * i;
                fma8(a0, wreg[i], xs[r]);
                fma8(a1, wreg[i], xs[512 + r]);
            }
#pragma unroll
            for (int i = 0; i < 8; i++)
#pragma unroll
                for (int s = 4; s < 32; s <<= 1) {
                    a0[i] += __shfl_xor_sync(~0u, a0[i], s);
                    a1[i] += __shfl_xor_sync(~0u, a1[i], s);
                }
            if (lane < 8) {
                float4* d = (float4*)(red + warp * 64 + lane * 8);
                if (lane < 4) { d[0] = make_float4(a0[0], a0[1], a0[2], a0[3]); d[1] = make_float4(a0[4], a0[5], a0[6], a0[7]); }
                else          { d[0] = make_float4(a1[0], a1[1], a1[2], a1[3]); d[1] = make_float4(a1[4], a1[5], a1[6], a1[7]); }
            }
            cbar();
            if (tid < 64) {
                float s = 0.f;
#pragma unroll
                for (int w = 0; w < 8; w++) s += red[w * 64 + tid];
                st_pub1(&g_q[(tid >> 5) * 4096 + cta * 32 + (tid & 31)], (packbf(0.f, s) & 0xffff0000u) | tag);
            }
        }
        if (tid == 0) TS(5);
        {
            uint4 v[8];
            int it = 0;
            while (true) {
                uint32_t bad = 0;
#pragma unroll
                for (int i = 0; i < 8; i++) v[i] = ld_poll4((const uint4*)g_q + i * 256 + tid);
#pragma unroll
                for (int i = 0; i < 8; i++) bad |= (v[i].x ^ tag) | (v[i].y ^ tag) | (v[i].z ^ tag) | (v[i].w ^ tag);
                if ((bad & 0xffffu) == 0) break;
                if (++it > SPIN_LIMIT) __trap();
                __nanosleep(200);
            }
#pragma unroll
            for (int i = 0; i < 8; i++)
                *(uint2*)(smem + OFF_Q + (i * 256 + tid) * 8) = make_uint2(__byte_perm(v[i].x, v[i].y, 0x7632), __byte_perm(v[i].z, v[i].w, 0x7632));
            cbar();
        }
        if (tid == 0) TS(6);

        const int g = lane >> 2, t = lane & 3;
        const uint32_t kE = g * 256 + t * 16 + (g & 1) * 64, kO = g * 256 + t * 16 + 64 - (g & 1) * 64;
        uint32_t voff[8], msk[8];
        {
            const int mi = lane >> 3, i = lane & 7;
            const uint32_t vb = 8192 + (8 * (mi & 1) + i) * 256 + 128 * ((mi & 1) ^ (mi >> 1));
#pragma unroll
            for (int c = 0; c < 8; c++) {
                voff[c] = vb + ((c + i) & 7) * 16;
                msk[c] = (((c + 2 * t) & 7) == g ? 0x0000ffffu : 0u) | (((c + 2 * t + 1) & 7) == g ? 0xffff0000u : 0u);
            }
        }
        const float SC = 0.08838834764831845f * 1.4426950408889634f;
        int st = warp; uint32_t ph = 0;
#pragma unroll 1
        for (int pass = WARM ? 0 : 1; pass < 2; pass++) {
        while (pass) {
            mbar_wait(bDone + st * 8, ph ^ 1);
            mbar_wait(bFull + st * 8, ph);
            const int u = meta[st].x;
            if (u < 0) break;
            const uint32_t base = sb + st * 16384;
            const uint32_t qa = sb + OFF_Q + (u >> 9) * 256 + t * 16;
            uint4 Q[4];
#pragma unroll
            for (int j = 0; j < 4; j++) Q[j] = lds128(qa + j * 64);
            float s[4][4];
#pragma unroll
            for (int n = 0; n < 4; n++) {
                s[n][0] = s[n][1] = s[n][2] = s[n][3] = 0.f;
#pragma unroll
                for (int j = 0; j < 4; j++) {
                    const uint4 kk = lds128(base + n * 2048 + ((j & 1) ? kO : kE) + (j >> 1) * 128);
                    mma(s[n], Q[j].x, Q[j ^ 1].x, Q[j].y, Q[j ^ 1].y, kk.x, kk.y);
                    mma(s[n], Q[j].z, Q[j ^ 1].z, Q[j].w, Q[j ^ 1].w, kk.z, kk.w);
                }
            }
            float mx = fmaxf(fmaxf(fmaxf(s[0][0], s[0][3]), fmaxf(s[1][0], s[1][3])), fmaxf(fmaxf(s[2][0], s[2][3]), fmaxf(s[3][0], s[3][3])));
            mx = fmaxf(mx, __shfl_xor_sync(~0u, mx, 1));
            mx = fmaxf(mx, __shfl_xor_sync(~0u, mx, 2));
            const float mu = mx * SC;
            uint32_t P[4];
            float l = 0.f;
#pragma unroll
            for (int n = 0; n < 4; n++) {
                const float p0 = ex2(fmaf(s[n][0], SC, -mu)), p1 = ex2(fmaf(s[n][3], SC, -mu));
                l += p0 + p1;
                P[n] = packbf(p0, p1);
            }
            l += __shfl_xor_sync(~0u, l, 1);
            l += __shfl_xor_sync(~0u, l, 2);
            float o[4][4];
#pragma unroll
            for (int n = 0; n < 4; n++) o[n][0] = o[n][1] = o[n][2] = o[n][3] = 0.f;
#pragma unroll
            for (int c = 0; c < 8; c++) {
#pragma unroll
                for (int T = 0; T < 2; T++) {
                    const uint4 vv = ldsm4t(base + voff[c] + T * 4096);
                    const uint32_t pl = P[2 * T] & msk[c], phh = P[2 * T + 1] & msk[c];
                    mma(o[2 * T], pl, 0u, 0u, phh, vv.x, vv.y);
                    mma(o[2 * T + 1], 0u, pl, phh, 0u, vv.z, vv.w);
                }
            }
            float* res = (float*)(smem + OFF_RES + st * 528);
            *(float2*)(res + 2 * lane) = make_float2((o[0][0] + o[1][0]) + (o[2][0] + o[3][0]), (o[0][1] + o[1][1]) + (o[2][1] + o[3][1]));
            *(float2*)(res + 64 + 2 * lane) = make_float2((o[0][2] + o[1][2]) + (o[2][2] + o[3][2]), (o[0][3] + o[1][3]) + (o[2][3] + o[3][3]));
            if (lane == 0) *(float2*)(res + 128) = make_float2(mu, l);
            __syncwarp();
            if (lane == 0) mbar_arrive(bDone + st * 8);
            st += 8;
            if (st >= NS) { st -= NS; ph ^= 1; }
        }
        if (cta < 128) {
            const int s0 = pass ? *(volatile int*)(smem + OFF_N) : 0;
            const uint32_t* coef = (const uint32_t*)(smem + OFF_COEF);
            float y[2][4];
            y[0][0] = y[0][1] = y[0][2] = y[0][3] = y[1][0] = y[1][1] = y[1][2] = y[1][3] = 0.f;
            const int mi = lane >> 3, wrow = 8 * (mi & 1) + (lane & 7);
            if (tid == 0) TS(7);
            if (pass) mbar_wait(bOfin, 0);
#pragma unroll
            for (int i = 0; i < 3; i++) {
                const uint32_t c0l = coef[i * 8 + t], c0h = coef[i * 8 + 4 + t], c1l = coef[24 + i * 8 + t], c1h = coef[24 + i * 8 + 4 + t];
                int sl = s0 + i; if (sl >= NS) sl -= NS;
                const uint32_t wb = (pass ? sb + sl * 16384 + (i == 0 ? min(wrow, nr - 1) : wrow) * 1024 : sb + OFF_Q) + warp * 128;
                if (pass) mbar_wait(bW + i * 8, 0);
#pragma unroll
                for (int c = 0; c < 8; c += 2) {
                    const uint4 vv = ldsm4t(wb + ((c + (mi >> 1) + lane) & 7) * 16);
                    mma(y[0], c0l & msk[c], c1l & msk[c], c0h & msk[c], c1h & msk[c], vv.x, vv.y);
                    mma(y[1], c0l & msk[c + 1], c1l & msk[c + 1], c0h & msk[c + 1], c1h & msk[c + 1], vv.z, vv.w);
                }
            }
            if (tid == 0) TS(8);
            uint2* yp = (uint2*)g_y;
            uint4 v = make_uint4(tag, tag, tag, tag);
            if (pass) {
                st_pub2(yp + (((tid >> 2) * 128 + cta) * 4 + (tid & 3)), tg(y[0][0] + y[1][0], tag), tg(y[0][1] + y[1][1], tag));
                st_pub2(yp + (((64 + (tid >> 2)) * 128 + cta) * 4 + (tid & 3)), tg(y[0][2] + y[1][2], tag), tg(y[0][3] + y[1][3], tag));
            }
            int it = 0;
            while (true) {
                if (pass) v = ld_poll4(&g_y[cta * 256 + tid]);
                if (((((v.x ^ tag) | (v.y ^ tag)) | ((v.z ^ tag) | (v.w ^ tag))) & 15u) == 0) break;
                if (++it > SPIN_LIMIT) __trap();
            }
            if (tid == 255) { TS(13); TSV(14, it); }
            float f0 = __uint_as_float(v.x), f1 = __uint_as_float(v.y), f2 = __uint_as_float(v.z), f3 = __uint_as_float(v.w);
            {
                const bool hi = lane & 2;
                const float s0_ = hi ? f0 : f2, s1_ = hi ? f1 : f3;
                f0 = (hi ? f2 : f0) + __shfl_xor_sync(~0u, s0_, 2);
                f1 = (hi ? f3 : f1) + __shfl_xor_sync(~0u, s1_, 2);
                const bool h2 = lane & 4;
                f0 = (h2 ? f1 : f0) + __shfl_xor_sync(~0u, h2 ? f0 : f1, 4);
                f0 += __shfl_xor_sync(~0u, f0, 8);
                f0 += __shfl_xor_sync(~0u, f0, 16);
            }
            if (lane < 8) red[warp * 8 + (lane & 1) * 4 + (lane & 2) + (lane >> 2)] = f0;
            cbar();
            if (tid < 8) {
                float s = 0.f;
#pragma unroll
                for (int w = 0; w < 8; w++) s += red[w * 8 + tid];
                if (pass) {
                    out[cta * 8 + tid] = __float2bfloat16(s);
                    if (tid == 0 && cta == 0) g_epoch = epoch + 1;
                }
                if (tid == 0) TS(9);
            }
        }
        }
    }
}

extern "C" void kernel_launch(void* const* d_in, const int* in_sizes, int n_in, void* d_out, int out_size) {
    (void)in_sizes; (void)n_in; (void)out_size;
    cudaFuncSetAttribute(fused_decode_kernel, cudaFuncAttributeMaxDynamicSharedMemorySize, SMEM_BYTES);
    fused_decode_kernel<<<G, NTHREADS, SMEM_BYTES, cudaStreamPerThread>>>(
        (const __nv_bfloat16*)d_in[0], (const __nv_bfloat16*)d_in[1], (const __nv_bfloat16*)d_in[2],
        (const __nv_bfloat16*)d_in[3], (const __nv_bfloat16*)d_in[4], (const __nv_bfloat16*)d_in[6],
        (const __nv_bfloat16*)d_in[7], (const __nv_bfloat16*)d_in[8], (const __nv_bfloat16*)d_in[9],
        (__nv_bfloat16*)d_out);
}
```

```cpp
#include <cuda_runtime.h>
#include <cuda_bf16.h>
#include <stdint.h>

#define NS 12
#define CAP 3
#define PSTAT 8

#define RING 8
#define WTO 20000
#define EAGER (2 * 132)
#define STAG 150
#define PTAG(bh) (((epoch % 15u) * (64 / RING) + (bh) / RING) % 15u + 1u)
static_assert(NS >= 8 && PSTAT - 1 >= CAP && PSTAT <= NS && CAP >= 3, "ring");
constexpr int G = 132;
constexpr int NUNITS = 64 * 512;
constexpr int NDRAW = NUNITS - G * PSTAT + 2 * G;
constexpr int NTHREADS = 448;
constexpr int DF = 1376;
constexpr uint32_t YTAG = 8u;
constexpr int SPIN_LIMIT = 1 << 22;

constexpr int OFF_RING = 0;
constexpr int OFF_Q = NS * 16384;
constexpr int OFF_RES = OFF_Q + 16384;
constexpr int OFF_X = OFF_RES + NS * 528;
constexpr int OFF_RED = OFF_X + 4096;
constexpr int OFF_COEF = OFF_RED + 2048;
constexpr int OFF_CMB = OFF_COEF + 192;
constexpr int OFF_META = OFF_CMB + 576;
constexpr int OFF_BAR = OFF_META + NS * 8;
constexpr int OFF_N = OFF_BAR + (3 * NS + 7) * 8;
constexpr int SMEM_BYTES = OFF_N + 16;
static_assert(SMEM_BYTES <= 232448, "smem");

__device__ unsigned g_epoch;
__device__ unsigned g_ctr;
__device__ uint32_t g_q[2 * 4096];
__device__ uint32_t g_h[2 * DF];
__device__ uint4 g_po[RING * 4 * G * 8];
__device__ uint2 g_pml[RING * G];
__device__ uint4 g_cons[64];
__device__ uint4 g_y[128 * 128 * 2];

__device__ __forceinline__ uint32_t s2u(const void* p) { return (uint32_t)__cvta_generic_to_shared(p); }
__device__ __forceinline__ void mbar_init(uint32_t b, int c) { asm volatile("mbarrier.init.shared::cta.b64 [%0], %1;" ::"r"(b), "r"(c) : "memory"); }
__device__ __forceinline__ void mbar_expect(uint32_t b, uint32_t bytes) { asm volatile("mbarrier.arrive.expect_tx.shared::cta.b64 _, [%0], %1;" ::"r"(b), "r"(bytes) : "memory"); }
__device__ __forceinline__ void mbar_expect_only(uint32_t b, uint32_t bytes) { asm volatile("mbarrier.expect_tx.shared::cta.b64 [%0], %1;" ::"r"(b), "r"(bytes) : "memory"); }
__device__ __forceinline__ void mbar_arrive(uint32_t b) { asm volatile("mbarrier.arrive.shared::cta.b64 _, [%0];" ::"r"(b) : "memory"); }
__device__ __forceinline__ void mbar_wait(uint32_t b, uint32_t ph) {
    uint32_t ok;
    int it = 0;
    do {
        asm volatile("{\n.reg .pred p;\nmbarrier.try_wait.parity.shared::cta.b64 p, [%1], %2;\nselp.u32 %0, 1, 0, p;\n}" : "=r"(ok) : "r"(b), "r"(ph) : "memory");
        if (++it > SPIN_LIMIT) __trap();
    } while (!ok);
}
__device__ __forceinline__ bool mbar_test(uint32_t b, uint32_t ph) {
    uint32_t ok;
    asm volatile("{\n.reg .pred p;\nmbarrier.test_wait.parity.shared::cta.b64 p, [%1], %2;\nselp.u32 %0, 1, 0, p;\n}" : "=r"(ok) : "r"(b), "r"(ph) : "memory");
    return ok;
}
__device__ __forceinline__ void bulk(uint32_t dst, const void* src, uint32_t bytes, uint32_t bar, uint64_t pol) {
    asm volatile("cp.async.bulk.shared::cluster.global.mbarrier::complete_tx::bytes.L2::cache_hint [%0], [%1], %2, [%3], %4;" ::"r"(dst), "l"(src), "r"(bytes), "r"(bar), "l"(pol) : "memory");
}
__device__ __forceinline__ uint64_t evict_first() {
    uint64_t pol;
    asm volatile("createpolicy.fractional.L2::evict_first.b64 %0, 1.0;" : "=l"(pol));
    return pol;
}
__device__ __forceinline__ uint4 lds128(uint32_t a) {
    uint4 v;
    asm volatile("ld.shared.v4.u32 {%0,%1,%2,%3}, [%4];" : "=r"(v.x), "=r"(v.y), "=r"(v.z), "=r"(v.w) : "r"(a));
    return v;
}
__device__ __forceinline__ uint4 ldsm4t(uint32_t a) {
    uint4 v;
    asm volatile("ldmatrix.sync.aligned.m8n8.x4.trans.shared.b16 {%0,%1,%2,%3}, [%4];" : "=r"(v.x), "=r"(v.y), "=r"(v.z), "=r"(v.w) : "r"(a));
    return v;
}
__device__ __forceinline__ void mma(float (&c)[4], uint32_t a0, uint32_t a1, uint32_t a2, uint32_t a3, uint32_t b0, uint32_t b1) {
    asm volatile("mma.sync.aligned.m16n8k16.row.col.f32.bf16.bf16.f32 {%0,%1,%2,%3}, {%4,%5,%6,%7}, {%8,%9}, {%0,%1,%2,%3};"
                 : "+f"(c[0]), "+f"(c[1]), "+f"(c[2]), "+f"(c[3]) : "r"(a0), "r"(a1), "r"(a2), "r"(a3), "r"(b0), "r"(b1));
}
__device__ __forceinline__ void mma_top(float (&c)[4], uint32_t a0, uint32_t a2, uint32_t b0, uint32_t b1) {
    asm volatile("{\n.reg .b32 u1, u3;\nmma.sync.aligned.m16n8k16.row.col.f32.bf16.bf16.f32 {%0,%1,%2,%3}, {%4,u1,%5,u3}, {%6,%7}, {%0,%1,%2,%3};\n}"
                 : "+f"(c[0]), "+f"(c[1]), "+f"(c[2]), "+f"(c[3]) : "r"(a0), "r"(a2), "r"(b0), "r"(b1));
}
__device__ __forceinline__ void put_q(unsigned char* q, int i, uint4 v) {
    uint32_t* d = (uint32_t*)(q + (i >> 4) * 128 + (i & 1) * 64 + (i & 6) * 8 + (i & 8) / 2);
    d[0] = __byte_perm(v.x, v.y, 0x7632);
    d[2] = __byte_perm(v.z, v.w, 0x7632);
}
__device__ __forceinline__ uint4 ldg_nc(const void* p) {
    uint4 v;
    asm volatile("ld.global.nc.L1::no_allocate.v4.u32 {%0,%1,%2,%3}, [%4];" : "=r"(v.x), "=r"(v.y), "=r"(v.z), "=r"(v.w) : "l"(p));
    return v;
}
__device__ __forceinline__ uint4 ld_poll4(const void* p) {
    uint4 v;
    asm volatile("ld.relaxed.gpu.global.v4.u32 {%0,%1,%2,%3}, [%4];" : "=r"(v.x), "=r"(v.y), "=r"(v.z), "=r"(v.w) : "l"(p) : "memory");
    return v;
}
__device__ __forceinline__ uint2 ld_poll2(const void* p) {
    uint2 v;
    asm volatile("ld.relaxed.gpu.global.v2.u32 {%0,%1}, [%2];" : "=r"(v.x), "=r"(v.y) : "l"(p) : "memory");
    return v;
}
__device__ __forceinline__ void repoll4(uint4& v, const void* p, uint32_t tag) {
    const uint32_t bad = ((v.x ^ tag) | (v.y ^ tag) | (v.z ^ tag) | (v.w ^ tag)) & 15u;
    asm volatile("{\n.reg .pred p;\nsetp.ne.u32 p, %5, 0;\n@p ld.relaxed.gpu.global.v4.u32 {%0,%1,%2,%3}, [%4];\n}"
                 : "+r"(v.x), "+r"(v.y), "+r"(v.z), "+r"(v.w) : "l"(p), "r"(bad) : "memory");
}
__device__ __forceinline__ void repoll2(uint2& v, const void* p, uint32_t tag) {
    const uint32_t bad = ((v.x ^ tag) | (v.y ^ tag)) & 15u;
    asm volatile("{\n.reg .pred p;\nsetp.ne.u32 p, %3, 0;\n@p ld.relaxed.gpu.global.v2.u32 {%0,%1}, [%2];\n}"
                 : "+r"(v.x), "+r"(v.y) : "l"(p), "r"(bad) : "memory");
}
__device__ __forceinline__ uint32_t ld_poll1(const void* p) {
    uint32_t v;
    asm volatile("ld.relaxed.gpu.global.u32 %0, [%1];" : "=r"(v) : "l"(p) : "memory");
    return v;
}
__device__ __forceinline__ void st_pub4(void* p, uint32_t a, uint32_t b, uint32_t c, uint32_t d) {
    asm volatile("st.relaxed.gpu.global.v4.u32 [%0], {%1,%2,%3,%4};" ::"l"(p), "r"(a), "r"(b), "r"(c), "r"(d) : "memory");
}
__device__ __forceinline__ void st_pub2(void* p, uint32_t a, uint32_t b) {
    asm volatile("st.relaxed.gpu.global.v2.u32 [%0], {%1,%2};" ::"l"(p), "r"(a), "r"(b) : "memory");
}
__device__ __forceinline__ void st_pub1(void* p, uint32_t a) {
    asm volatile("st.relaxed.gpu.global.u32 [%0], %1;" ::"l"(p), "r"(a) : "memory");
}
__device__ __forceinline__ int ticket(unsigned* p) {
    int v;
    asm volatile("atom.relaxed.gpu.global.inc.u32 %0, [%1], %2;" : "=r"(v) : "l"(p), "n"(NDRAW - 1) : "memory");
    return v;
}
__device__ __forceinline__ uint32_t tg(float v, uint32_t tag) { return (__float_as_uint(v) & ~15u) | tag; }
__device__ __forceinline__ float blo(uint32_t v) { return __uint_as_float(v << 16); }
__device__ __forceinline__ float bhi(uint32_t v) { return __uint_as_float(v & 0xffff0000u); }
__device__ __forceinline__ float ex2(float x) { float r; asm("ex2.approx.ftz.f32 %0, %1;" : "=f"(r) : "f"(x)); return r; }
__device__ __forceinline__ uint32_t packbf(float lo, float hi) {
    uint32_t r;
    asm("cvt.rn.bf16x2.f32 %0, %1, %2;" : "=r"(r) : "f"(hi), "f"(lo));
    return r;
}
__device__ __forceinline__ void fma8(float (&a)[8], uint4 w, float x) {
    a[0] = fmaf(blo(w.x), x, a[0]); a[1] = fmaf(bhi(w.x), x, a[1]);
    a[2] = fmaf(blo(w.y), x, a[2]); a[3] = fmaf(bhi(w.y), x, a[3]);
    a[4] = fmaf(blo(w.z), x, a[4]); a[5] = fmaf(bhi(w.z), x, a[5]);
    a[6] = fmaf(blo(w.w), x, a[6]); a[7] = fmaf(bhi(w.w), x, a[7]);
}
__device__ __forceinline__ void spin(int cyc) { const uint32_t c0 = clock(); while ((uint32_t)clock() - c0 < (uint32_t)cyc) {} }
__device__ __forceinline__ void cbar() { asm volatile("bar.sync 1, 256;" ::: "memory"); }

__global__ void __launch_bounds__(NTHREADS, 1)
fused_decode_kernel(const __nv_bfloat16* __restrict__ x, const __nv_bfloat16* __restrict__ Kc, const __nv_bfloat16* __restrict__ Vc,
                    const __nv_bfloat16* __restrict__ wq, const __nv_bfloat16* __restrict__ wo,
                    const __nv_bfloat16* __restrict__ wg, const __nv_bfloat16* __restrict__ wu,
                    const __nv_bfloat16* __restrict__ wd, const __nv_bfloat16* __restrict__ gw,
                    __nv_bfloat16* __restrict__ out) {
    extern __shared__ __align__(1024) unsigned char smem[];
    const int tid = threadIdx.x, lane = tid & 31, warp = tid >> 5, cta = blockIdx.x;
    const uint32_t sb = s2u(smem);
    const uint32_t bFull = sb + OFF_BAR, bDone = bFull + NS * 8, bEmpty = bDone + NS * 8, bW = bEmpty + NS * 8,
                   bHfin = bW + 8, bNop = bW + 16, bCb = bW + 24, bOfin = bCb + 16, bQ = bOfin + 8;
    float* xs = (float*)(smem + OFF_X);
    volatile int2* meta = (volatile int2*)(smem + OFF_META);
    const int r0 = (cta * 43) >> 2, nr = (((cta + 1) * 43) >> 2) - r0;

    uint4 wreg[8];
    int pw;
    asm volatile("shr.u32 %0, %1, 5;" : "=r"(pw) : "r"(tid));
    if (pw == 8) {
        if (lane == 0) {
#pragma unroll
            for (int i = 0; i < 3 * NS + 7; i++) mbar_init(bFull + i * 8, i == 3 * NS + 6 ? 2 : 1);
            asm volatile("fence.mbarrier_init.release.cluster;" ::: "memory");
        }
        __syncwarp();
        asm volatile("bar.arrive 3, %0;" ::"n"(NTHREADS) : "memory");
    } else if (warp < 8) {
        if (cta < 128) {
            const __nv_bfloat16* p = wq + (size_t)(tid >> 2) * 8 * 4096 + cta * 32 + (tid & 3) * 8;
#pragma unroll
            for (int i = 0; i < 8; i++) wreg[i] = ldg_nc(p + (size_t)i * 4096);
        }
    } else if (pw >= 10) {
        wreg[0] = ldg_nc(x + (tid - 320) * 8);
        wreg[1].x = ld_poll1(&g_epoch);
    }
    if (warp != 8) asm volatile("bar.sync 3, %0;" ::"n"(NTHREADS) : "memory");

    if (warp == 8) {
        if (lane == 0) {
            const uint64_t pol = evict_first();
            int ta = cta - G * PSTAT, tb = ta + G, tc;
            int st = 0, cst = NS - CAP;
            uint32_t eph = 1, cph = 1;
            const __nv_bfloat16 *Kp = Kc + (size_t)G * PSTAT * 4096, *Vp = Vc + (size_t)G * PSTAT * 4096;
#define STEP(cur, nxt, nn)                                                                   \
            if (cur >= NUNITS - G * PSTAT) break;                                            \
            if (cur < -2 * G) nn = cur + 2 * G; else nn = ticket(&g_ctr);                    \
            if (cur < NUNITS - G * PSTAT - EAGER) mbar_wait(bFull + cst * 8, cph);           \
            mbar_wait(bEmpty + st * 8, eph);                                                 \
            mbar_expect_only(bFull + st * 8, 16384);                                         \
            bulk(sb + st * 16384, Kp + (ptrdiff_t)cur * 4096, 8192, bFull + st * 8, pol);    \
            bulk(sb + st * 16384 + 8192, Vp + (ptrdiff_t)cur * 4096, 8192, bFull + st * 8, pol); \
            meta[st].x = cur + G * PSTAT; meta[st].y = nxt + G * PSTAT;                      \
            mbar_arrive(bFull + st * 8);                                                     \
            if (++st == NS) { st = 0; eph ^= 1; }                                            \
            if (++cst == NS) { cst = 0; cph ^= 1; }
            while (true) {
                STEP(ta, tb, tc)
                STEP(tb, tc, ta)
                STEP(tc, ta, tb)
            }
#undef STEP
            const uint32_t tend = clock();
            *(volatile int*)(smem + OFF_N) = st;
            const int last = st == 0 ? NS - 1 : st - 1;
            const uint32_t lph = st == 0 ? eph : eph ^ 1;
            int wsl = st;
#pragma unroll 1
            for (int i = 0; i < 8; i++) {
                mbar_wait(bEmpty + st * 8, eph);
                meta[st].x = -1;
                mbar_arrive(bFull + st * 8);
                if (++st == NS) { st = 0; eph ^= 1; }
                if (i == 2 && cta < 128) {
                    mbar_expect(bW, nr * 1024 + 32768);
                    const __nv_bfloat16* src = wd + (size_t)r0 * 512;
                    uint32_t bytes = nr * 1024;
                    while (!mbar_test(bFull + last * 8, lph) && (uint32_t)clock() - tend < WTO) {}
#pragma unroll 1
                    for (int j = 0; j < 3; j++) {
                        bulk(sb + wsl * 16384, src, bytes, bW, pol);
                        src = wo + (size_t)(cta * 32 + j * 16) * 512;
                        bytes = 16384;
                        if (++wsl == NS) wsl = 0;
                    }
                }
            }
        }
    } else if (warp == 9) {
        const unsigned epoch = ld_poll1(&g_epoch);
        float m = -1e30f, l = 0.f, o0 = 0.f, o1 = 0.f, o2 = 0.f, o3 = 0.f;
        int st = 0; uint32_t ph = 0;
        const int myh = cta >> 2;
        uint4 cons = make_uint4(0u, 0u, 0u, 0u);
        bool live = false;
        while (true) {
            mbar_wait(live ? bDone + st * 8 : bOfin, live ? ph : 1u);
            const int u = live ? meta[st].x : 0, nx = live ? meta[st].y : 0;
            const float* res = (const float*)(smem + OFF_RES + st * 528);
            const float4 v = *(const float4*)(res + lane * 4);
            const float2 ml = *(const float2*)(res + 128);
            __syncwarp();
            if (lane == 0) mbar_arrive(live ? bEmpty + st * 8 : bNop);
            const float mn = fmaxf(m, ml.x);
            const float a = ex2(m - mn), b = ex2(ml.x - mn);
            m = mn;
            l = l * a + ml.y * b;
            o0 = o0 * a + v.x * b; o1 = o1 * a + v.y * b; o2 = o2 * a + v.z * b; o3 = o3 * a + v.w * b;
            const int nb = min(nx >> 9, 64);
            for (int bh = u >> 9; bh < nb; bh++) {
                const uint32_t ptag = PTAG(bh);
                if (bh >= RING) {
                    int it = 0;
                    while (cons.x != epoch + 1 || cons.y != epoch + 1 || cons.z != epoch + 1 || cons.w != epoch + 1) {
                        cons = ld_poll4(&g_cons[bh - RING]);
                        if (++it > SPIN_LIMIT) __trap();
                    }
                }
                if (bh == 32 && cta < 128) {
#pragma unroll
                    for (int i = 0; i < 8; i++) st_pub4(&g_y[cta * 256 + i * 32 + lane], 0u, 0u, 0u, 0u);
                    __threadfence();
                    __syncwarp();
                }
                st_pub4(&g_po[(((bh % RING) * 4 + (lane >> 3)) * G + cta) * 8 + (lane & 7)], tg(o0, ptag), tg(o1, ptag), tg(o2, ptag), tg(o3, ptag));
                if (lane == 0) {
                    st_pub2(&g_pml[(bh % RING) * G + cta], tg(m, ptag), tg(l, ptag));
                    if ((bh & 31) == myh) mbar_arrive(bCb + (bh >> 5) * 8);
                }
                if (bh + 1 >= RING && bh < 63) cons = ld_poll4(&g_cons[bh + 1 - RING]);
                m = -1e30f; l = 0.f; o0 = o1 = o2 = o3 = 0.f;
            }
            if (nb == 64) break;
            if (!live) { live = true; m = -1e30f; l = 0.f; o0 = o1 = o2 = o3 = 0.f; continue; }
            if (++st == NS) { st = 0; ph ^= 1; }
        }
    } else if (warp >= 10) {
        const int cw = warp - 10;
        const uint4 xr0 = wreg[0];
        const unsigned epoch = wreg[1].x;
        const uint32_t tag = epoch % 15u + 1u;
        {
            if (tid == 320) *(volatile uint32_t*)(smem + OFF_N + 4) = tag;
            float4* d = (float4*)(xs + (tid - 320) * 8);
            d[0] = make_float4(blo(xr0.x), bhi(xr0.x), blo(xr0.y), bhi(xr0.y));
            d[1] = make_float4(blo(xr0.z), bhi(xr0.z), blo(xr0.w), bhi(xr0.w));
            asm volatile("bar.arrive 4, 384;" ::: "memory");
            asm volatile("bar.sync 2, 128;" ::: "memory");
        }
        if (cw >= 2) {
            asm volatile("bar.sync 5, 320;" ::: "memory");
#pragma unroll 1
            for (int j = 0; j < 4; j++) {
                uint4 v[7];
                const int i0 = 256 + j * 448 + tid - 384;
                int it = 0;
                while (true) {
                    uint32_t bad = 0;
#pragma unroll
                    for (int i = 0; i < 7; i++) v[i] = ld_poll4((const uint4*)g_q + i0 + i * 64);
#pragma unroll
                    for (int i = 0; i < 7; i++) bad |= (v[i].x ^ tag) | (v[i].y ^ tag) | (v[i].z ^ tag) | (v[i].w ^ tag);
                    if ((bad & 0xffffu) == 0) break;
                    if (++it > SPIN_LIMIT) __trap();
                    __nanosleep(200);
                }
#pragma unroll
                for (int i = 0; i < 7; i++)
                    put_q(smem + OFF_Q, i0 + i * 64, v[i]);
            }
            __syncwarp();
            if (lane == 0) mbar_arrive(bQ);
        }
        if (cta >= G - 11) {
            const int f0 = min((cta - (G - 11)) * 128 + (lane & 15) * 8, DF - 8), b = lane >> 4;
            float ag[2][8], au[2][8];
#pragma unroll
            for (int i = 0; i < 8; i++) ag[0][i] = ag[1][i] = au[0][i] = au[1][i] = 0.f;
            const size_t off = (size_t)(cw * 128 + b) * DF + f0;
#pragma unroll 1
            for (int it = 0; it < 8; it++) {
                uint4 wa[8], wb[8];
#pragma unroll
                for (int i = 0; i < 8; i++) {
                    wa[i] = ldg_nc(wg + off + (size_t)(it * 16 + i * 2) * DF);
                    wb[i] = ldg_nc(wu + off + (size_t)(it * 16 + i * 2) * DF);
                }
#pragma unroll
                for (int i = 0; i < 8; i++) {
                    const int r = cw * 128 + it * 16 + i * 2 + b;
                    const float x0 = xs[r], x1 = xs[512 + r];
                    fma8(ag[0], wa[i], x0); fma8(ag[1], wa[i], x1);
                    fma8(au[0], wb[i], x0); fma8(au[1], wb[i], x1);
                }
            }
            float gv[8], uv[8];
#pragma unroll
            for (int i = 0; i < 8; i++) {
                gv[i] = (b ? ag[1][i] : ag[0][i]) + __shfl_xor_sync(~0u, b ? ag[0][i] : ag[1][i], 16);
                uv[i] = (b ? au[1][i] : au[0][i]) + __shfl_xor_sync(~0u, b ? au[0][i] : au[1][i], 16);
            }
            float* acc = (float*)(smem + OFF_RED) + lane;
#pragma unroll 1
            for (int k = 0; k < 4; k++) {
                if (((cw + 2) & 3) == k) {
#pragma unroll
                    for (int i = 0; i < 8; i++) {
                        if (k > 0) { gv[i] += acc[i * 64]; uv[i] += acc[i * 64 + 32]; }
                        acc[i * 64] = gv[i]; acc[i * 64 + 32] = uv[i];
                    }
                }
                asm volatile("bar.sync 2, 128;" ::: "memory");
            }
            if (cw == 1) {
                uint32_t hv[8];
#pragma unroll
                for (int i = 0; i < 8; i++) {
                    const float t = tanhf(0.7978845608028654f * (gv[i] + 0.044715f * gv[i] * gv[i] * gv[i]));
                    hv[i] = tg(0.5f * gv[i] * (1.f + t) * uv[i], tag);
                }
                uint32_t* d = &g_h[b * DF + f0];
                st_pub4(d, hv[0], hv[1], hv[2], hv[3]);
                st_pub4(d + 4, hv[4], hv[5], hv[6], hv[7]);
            }
        }
        if (cta < 128) {
            __nv_bfloat16* coef = (__nv_bfloat16*)(smem + OFF_COEF);
            float* cmb = (float*)(smem + OFF_CMB);
            float gate0 = 0.f, gate1 = 0.f;
            if (cw == 0) {
                const uint4 w0 = ldg_nc(gw + lane * 16), w1 = ldg_nc(gw + lane * 16 + 8);
                const uint32_t w[8] = {w0.x, w0.y, w0.z, w0.w, w1.x, w1.y, w1.z, w1.w};
#pragma unroll
                for (int i = 0; i < 8; i++) {
                    gate0 = fmaf(blo(w[i]), xs[lane * 16 + 2 * i], gate0);
                    gate0 = fmaf(bhi(w[i]), xs[lane * 16 + 2 * i + 1], gate0);
                    gate1 = fmaf(blo(w[i]), xs[512 + lane * 16 + 2 * i], gate1);
                    gate1 = fmaf(bhi(w[i]), xs[512 + lane * 16 + 2 * i + 1], gate1);
                }
#pragma unroll
                for (int k = 1; k < 32; k <<= 1) {
                    gate0 += __shfl_xor_sync(~0u, gate0, k);
                    gate1 += __shfl_xor_sync(~0u, gate1, k);
                }
                gate0 = 1.f / (1.f + __expf(-gate0));
                gate1 = 1.f / (1.f + __expf(-gate1));
            }
#pragma unroll 1
            for (int b = 0; b < 2; b++) {
                const int bh = b * 32 + (cta >> 2);
                if (b == 1 && cw == 0) {
                    const int r = lane & 15, bb = lane >> 4;
                    uint32_t hv = tag;
                    if (r < nr) {
                        int it = 0;
                        do {
                            hv = ld_poll1(&g_h[bb * DF + r0 + r]);
                            if (++it > SPIN_LIMIT) __trap();
                            if ((hv & 15u) != tag) __nanosleep(1000);
                        } while ((hv & 15u) != tag);
                    }
                    coef[bb * 48 + r] = __float2bfloat16(r < nr ? __uint_as_float(hv) * (1.f - (bb ? gate1 : gate0)) : 0.f);
                    __syncwarp();
                    if (lane == 0) mbar_arrive(bHfin);
                }
                mbar_wait(bCb + b * 8, 0);
                const uint4* po = &g_po[((bh % RING) * 4 + (cta & 3)) * G * 8];
                const uint2* pm = &g_pml[(bh % RING) * G];
                const uint32_t ptag = PTAG(bh);
                uint4 v[9];
                uint2 ml = make_uint2(0u, 0u), mle = ml;
#pragma unroll
                for (int i = 0; i < 9; i++) v[i] = make_uint4(0u, 0u, 0u, 0u);
                int it = 0;
                while (true) {
                    repoll2(ml, pm + cw * 32 + lane, ptag);
                    repoll2(mle, pm + 128 + cw, ptag);
#pragma unroll
                    for (int i = 0; i < 8; i++) repoll4(v[i], po + cw * 256 + i * 32 + lane, ptag);
                    repoll4(v[8], po + (128 + cw) * 8 + (lane & 7), ptag);
                    uint32_t bad = (v[8].x ^ ptag) | (v[8].y ^ ptag) | (v[8].z ^ ptag) | (v[8].w ^ ptag);
#pragma unroll
                    for (int i = 7; i >= 0; i--) bad |= (v[i].x ^ ptag) | (v[i].y ^ ptag) | (v[i].z ^ ptag) | (v[i].w ^ ptag);
                    bad |= (ml.x ^ ptag) | (ml.y ^ ptag) | (mle.x ^ ptag) | (mle.y ^ ptag);
                    const bool ok = !__any_sync(~0u, (bad & 15u) != 0);
                    if (ok) {
                        int key = __float_as_int(fmaxf(__uint_as_float(ml.x), __uint_as_float(mle.x)));
                        key = __reduce_max_sync(~0u, key ^ ((key >> 31) & 0x7fffffff));
                        const float M = __int_as_float(key ^ ((key >> 31) & 0x7fffffff));
                        const float w = ex2(__uint_as_float(ml.x) - M), wl = w * __uint_as_float(ml.y & ~15u);
                        const float we = lane < 8 ? ex2(__uint_as_float(mle.x) - M) : 0.f;
                        float L = we * __uint_as_float(mle.y & ~15u);
                        float o0 = we * __uint_as_float(v[8].x), o1 = we * __uint_as_float(v[8].y), o2 = we * __uint_as_float(v[8].z), o3 = we * __uint_as_float(v[8].w);
#pragma unroll
                        for (int i = 0; i < 8; i++) {
                            const float wi = __shfl_sync(~0u, w, 4 * i + (lane >> 3));
                            L += __shfl_sync(~0u, wl, 4 * i + (lane >> 3));
                            o0 = fmaf(wi, __uint_as_float(v[i].x), o0); o1 = fmaf(wi, __uint_as_float(v[i].y), o1);
                            o2 = fmaf(wi, __uint_as_float(v[i].z), o2); o3 = fmaf(wi, __uint_as_float(v[i].w), o3);
                        }
#pragma unroll
                        for (int k = 8; k < 32; k <<= 1) {
                            o0 += __shfl_xor_sync(~0u, o0, k); o1 += __shfl_xor_sync(~0u, o1, k);
                            o2 += __shfl_xor_sync(~0u, o2, k); o3 += __shfl_xor_sync(~0u, o3, k);
                            L += __shfl_xor_sync(~0u, L, k);
                        }
                        if (lane < 8) *(float4*)(cmb + cw * 36 + lane * 4) = make_float4(o0, o1, o2, o3);
                        if (lane == 8) *(float2*)(cmb + cw * 36 + 32) = make_float2(M, L);
                    }
                    if (ok) break;
                    if (++it > SPIN_LIMIT) __trap();
                }
                __syncwarp();
                asm volatile("bar.sync 2, 128;" ::: "memory");
                if (cw == 0) {
                    {
                        const float2 a0 = *(const float2*)(cmb + 32), a1 = *(const float2*)(cmb + 68), a2 = *(const float2*)(cmb + 104), a3 = *(const float2*)(cmb + 140);
                        const float MM = fmaxf(fmaxf(a0.x, a1.x), fmaxf(a2.x, a3.x));
                        const float e0 = ex2(a0.x - MM), e1 = ex2(a1.x - MM), e2 = ex2(a2.x - MM), e3 = ex2(a3.x - MM);
                        const float LL = (e0 * a0.y + e1 * a1.y) + (e2 * a2.y + e3 * a3.y);
                        const float o = (e0 * cmb[lane] + e1 * cmb[36 + lane]) + (e2 * cmb[72 + lane] + e3 * cmb[108 + lane]);
                        coef[b * 48 + 16 + lane] = __float2bfloat16(o * __fdividef(b ? gate1 : gate0, LL));
                        __syncwarp();
                        if (b == 1 && lane == 0) mbar_arrive(bOfin);
                    }
                    if (lane == 0) st_pub1((uint32_t*)&g_cons[bh] + (cta & 3), epoch + 1);
                    if (lane == 0 && b == 1 && cta == 127) g_epoch = epoch + 1;
                }
                if (b == 0) asm volatile("bar.sync 2, 128;" ::: "memory");
            }
        }
    } else {
        float* red = (float*)(smem + OFF_RED);
        const int g = lane >> 2, t = lane & 3;
        const uint32_t kE = g * 256 + t * 16 + (g & 1) * 64, kO = g * 256 + t * 16 + 64 - (g & 1) * 64;
        uint32_t voff[8], msk[8];
        {
            const int mi = lane >> 3, i = lane & 7;
            const uint32_t vb = 8192 + (8 * (mi & 1) + i) * 256 + 128 * (mi >> 1);
#pragma unroll
            for (int c = 0; c < 8; c++) {
                voff[c] = vb + ((c + i) & 7) * 16;
                msk[c] = (((c + 2 * t) & 7) == g ? 0x0000ffffu : 0u) | (((c + 2 * t + 1) & 7) == g ? 0xffff0000u : 0u);
            }
        }
        const float SC = 0.08838834764831845f * 1.4426950408889634f;
        int st = warp, qlim = 8 * 512; uint32_t ph = 0;
#pragma unroll 1
        for (int pass = 0; pass < 2; pass++) {
        if (pass) {
        asm volatile("bar.sync 4, 384;" ::: "memory");
        const uint32_t tag = *(volatile uint32_t*)(smem + OFF_N + 4);
        if (cta < 128) {
            float a0[8], a1[8];
#pragma unroll
            for (int i = 0; i < 8; i++) a0[i] = a1[i] = 0.f;
#pragma unroll
            for (int i = 0; i < 8; i++) {
                asm volatile("" : "+r"(wreg[i].x), "+r"(wreg[i].y), "+r"(wreg[i].z), "+r"(wreg[i].w));
                fma8(a0, wreg[i], xs[(tid >> 2) * 8 + i]);
                fma8(a1, wreg[i], xs[512 + (tid >> 2) * 8 + i]);
            }
#pragma unroll
            for (int i = 0; i < 8; i++)
#pragma unroll
                for (int s = 4; s < 32; s <<= 1) {
                    a0[i] += __shfl_xor_sync(~0u, a0[i], s);
                    a1[i] += __shfl_xor_sync(~0u, a1[i], s);
                }
            if (lane < 8) {
                float4* d = (float4*)(red + warp * 64 + lane * 8);
                if (lane < 4) { d[0] = make_float4(a0[0], a0[1], a0[2], a0[3]); d[1] = make_float4(a0[4], a0[5], a0[6], a0[7]); }
                else          { d[0] = make_float4(a1[0], a1[1], a1[2], a1[3]); d[1] = make_float4(a1[4], a1[5], a1[6], a1[7]); }
            }
            cbar();
            if (tid < 64) {
                float s = 0.f;
#pragma unroll
                for (int w = 0; w < 8; w++) s += red[w * 64 + tid];
                st_pub1(&g_q[(tid >> 5) * 4096 + cta * 32 + (tid & 31)], (packbf(0.f, s) & 0xffff0000u) | tag);
            }
        }
            uint4 v;
            int it = 0;
            do {
                v = ld_poll4((const uint4*)g_q + tid);
                if (++it > SPIN_LIMIT) __trap();
            } while ((((v.x ^ tag) | (v.y ^ tag) | (v.z ^ tag) | (v.w ^ tag)) & 0xffffu) != 0);
            put_q(smem + OFF_Q, tid, v);
            asm volatile("bar.sync 5, 320;" ::: "memory");
        }

        while (true) {
            mbar_wait(bDone + st * 8, ph ^ 1);
            mbar_wait((pass ? bFull : bDone) + st * 8, pass ? ph : 1u);
            const int u = pass ? meta[st].x : 0;
            if (u < 0) break;
            if (u >= qlim) { mbar_wait(bQ, 0); qlim = NUNITS; }
            const uint32_t base = sb + st * 16384;
            const uint32_t qa = sb + OFF_Q + (u >> 9) * 256 + t * 16;
            uint4 Q[4];
#pragma unroll
            for (int j = 0; j < 4; j++) Q[j] = lds128(qa + j * 64);
            float s[2][4][4];
#pragma unroll
            for (int n = 0; n < 8; n++) s[n >> 2][n & 3][0] = s[n >> 2][n & 3][1] = s[n >> 2][n & 3][2] = s[n >> 2][n & 3][3] = 0.f;
#pragma unroll
            for (int j = 0; j < 4; j++) {
#pragma unroll
                for (int n = 0; n < 4; n++) {
                    const uint4 kk = lds128(base + n * 2048 + ((j & 1) ? kO : kE) + (j >> 1) * 128);
                    mma(s[j & 1][n], Q[j & 2].x, Q[j & 2].y, Q[j & 2].z, Q[j & 2].w, kk.x, kk.y);
                    mma(s[j & 1][n], Q[j | 1].x, Q[j | 1].y, Q[j | 1].z, Q[j | 1].w, kk.z, kk.w);
                }
            }
            float sa[4], sc[4];
#pragma unroll
            for (int n = 0; n < 4; n++) { sa[n] = s[0][n][0] + s[1][n][2]; sc[n] = s[0][n][3] + s[1][n][1]; }
            float mx = fmaxf(fmaxf(fmaxf(sa[0], sc[0]), fmaxf(sa[1], sc[1])), fmaxf(fmaxf(sa[2], sc[2]), fmaxf(sa[3], sc[3])));
            mx = fmaxf(mx, __shfl_xor_sync(~0u, mx, 1));
            mx = fmaxf(mx, __shfl_xor_sync(~0u, mx, 2));
            const float mu = mx * SC;
            uint32_t P[4];
            float l = 0.f;
#pragma unroll
            for (int n = 0; n < 4; n++) {
                const float p0 = ex2(fmaf(sa[n], SC, -mu)), p1 = ex2(fmaf(sc[n], SC, -mu));
                l += p0 + p1;
                P[n] = packbf(p0, p1);
            }
            l += __shfl_xor_sync(~0u, l, 1);
            l += __shfl_xor_sync(~0u, l, 2);
            float o[4][4];
#pragma unroll
            for (int n = 0; n < 4; n++) o[n][0] = o[n][1] = o[n][2] = o[n][3] = 0.f;
#pragma unroll
            for (int c = 0; c < 8; c++) {
#pragma unroll
                for (int T = 0; T < 2; T++) {
                    const uint4 vv = ldsm4t(base + voff[c] + T * 4096);
                    const uint32_t pl = P[2 * T] & msk[c], phh = P[2 * T + 1] & msk[c];
                    mma_top(o[2 * T], pl, phh, vv.x, vv.y);
                    mma_top(o[2 * T + 1], pl, phh, vv.z, vv.w);
                }
            }
            float* res = (float*)(smem + OFF_RES + st * 528);
            *(float2*)(res + 2 * lane) = make_float2(o[0][0] + o[2][0], o[0][1] + o[2][1]);
            *(float2*)(res + 64 + 2 * lane) = make_float2(o[1][0] + o[3][0], o[1][1] + o[3][1]);
            if (lane == 0) *(float2*)(res + 128) = make_float2(mu, l);
            __syncwarp();
            if (lane == 0) mbar_arrive(pass ? bDone + st * 8 : bNop);
            if (!pass) break;
            st += 8;
            if (st >= NS) { st -= NS; ph ^= 1; }
        }
        }
#pragma unroll 1
        for (int pass = mbar_test(bW, 0) ? 1 : 0; pass < 2; pass++) {
        if (cta < 128) {
            const int s0 = pass ? *(volatile int*)(smem + OFF_N) : 0;
            const uint32_t* coef = (const uint32_t*)(smem + OFF_COEF);
            float y[4][4];
#pragma unroll
            for (int i = 0; i < 4; i++) y[i][0] = y[i][1] = y[i][2] = y[i][3] = 0.f;
            const int mi = lane >> 3, wrow = 8 * (mi & 1) + (lane & 7);
            if (pass) { mbar_wait(bW, 0); mbar_wait(bHfin, 0); }
            uint4 vv[3][4];
#pragma unroll
            for (int i = 0; i < 3; i++) {
                int sl = s0 + i; if (sl >= NS) sl -= NS;
                const uint32_t wb = (pass ? sb + sl * 16384 + (i == 0 ? min(wrow, nr - 1) : wrow) * 1024 : sb + OFF_Q) + warp * 128;
#pragma unroll
                for (int c = 0; c < 4; c++) vv[i][c] = ldsm4t(wb + ((2 * c + (mi >> 1) + lane) & 7) * 16);
            }
            uint32_t cf[3][4];
#pragma unroll
            for (int i = 0; i < 3; i++) { cf[i][0] = coef[i * 8 + t]; cf[i][2] = coef[i * 8 + 4 + t]; }
            cf[0][1] = coef[24 + t]; cf[0][3] = coef[28 + t];
#pragma unroll
            for (int i = 0; i < 3; i++) {
                if (i == 1) {
                    if (pass) mbar_wait(bOfin, 0);
                    cf[1][1] = coef[32 + t]; cf[1][3] = coef[36 + t]; cf[2][1] = coef[40 + t]; cf[2][3] = coef[44 + t];
                }
#pragma unroll
                for (int c = 0; c < 8; c += 2) {
                    mma(y[c & 2], cf[i][0] & msk[c], cf[i][1] & msk[c], cf[i][2] & msk[c], cf[i][3] & msk[c], vv[i][c >> 1].x, vv[i][c >> 1].y);
                    mma(y[(c & 2) + 1], cf[i][0] & msk[c + 1], cf[i][1] & msk[c + 1], cf[i][2] & msk[c + 1], cf[i][3] & msk[c + 1], vv[i][c >> 1].z, vv[i][c >> 1].w);
                }
            }
            uint2* yp = (uint2*)g_y;
            uint4 v;
            if (pass) {
                st_pub2(yp + (((64 + (tid >> 2)) * 128 + cta) * 4 + (tid & 3)), tg((y[0][2] + y[1][2]) + (y[2][2] + y[3][2]), YTAG), tg((y[0][3] + y[1][3]) + (y[2][3] + y[3][3]), YTAG));
                st_pub2(yp + (((tid >> 2) * 128 + cta) * 4 + (tid & 3)), tg((y[0][0] + y[1][0]) + (y[2][0] + y[3][0]), YTAG), tg((y[0][1] + y[1][1]) + (y[2][1] + y[3][1]), YTAG));
            }
            int it = 0;
            {
                const uint4* src = &g_y[cta * 256 + tid];
#define YOK(q) __all_sync(~0u, (((q.x & q.y) & (q.z & q.w)) & YTAG) != 0)
                uint4 p0 = make_uint4(YTAG, YTAG, YTAG, YTAG), p1 = p0, p2 = p0;
                if (pass) {
                    p0 = ld_poll4(src);
                    spin(STAG);
                    p1 = ld_poll4(src);
                    spin(STAG);
                }
                while (true) {
                    if (pass) p2 = ld_poll4(src);
                    if (YOK(p0)) { v = p0; break; }
                    p0 = ld_poll4(src);
                    if (YOK(p1)) { v = p1; break; }
                    p1 = ld_poll4(src);
                    if (YOK(p2)) { v = p2; break; }
                    if (++it > SPIN_LIMIT) __trap();
                }
#undef YOK
            }
            float f0 = __uint_as_float(v.x), f1 = __uint_as_float(v.y), f2 = __uint_as_float(v.z), f3 = __uint_as_float(v.w);
            {
                const bool hi = lane & 2;
                const float s0_ = hi ? f0 : f2, s1_ = hi ? f1 : f3;
                f0 = (hi ? f2 : f0) + __shfl_xor_sync(~0u, s0_, 2);
                f1 = (hi ? f3 : f1) + __shfl_xor_sync(~0u, s1_, 2);
                const bool h2 = lane & 4;
                f0 = (h2 ? f1 : f0) + __shfl_xor_sync(~0u, h2 ? f0 : f1, 4);
                f0 += __shfl_xor_sync(~0u, f0, 8);
                f0 += __shfl_xor_sync(~0u, f0, 16);
            }
            if (lane < 8 && pass) red[warp * 8 + (lane & 1) * 4 + (lane & 2) + (lane >> 2)] = f0;
            if (pass) cbar();
            if (tid < 8) {
                float s = 0.f;
#pragma unroll
                for (int w = 0; w < 8; w++) s += red[w * 8 + tid];
                if (pass) out[cta * 8 + tid] = __float2bfloat16(s);
            }
        }
        }
    }
}

extern "C" void kernel_launch(void* const* d_in, const int* in_sizes, int n_in, void* d_out, int out_size) {
    (void)in_sizes; (void)n_in; (void)out_size;
    cudaFuncSetAttribute(fused_decode_kernel, cudaFuncAttributeMaxDynamicSharedMemorySize, SMEM_BYTES);
    fused_decode_kernel<<<G, NTHREADS, SMEM_BYTES, cudaStreamPerThread>>>(
        (const __nv_bfloat16*)d_in[0], (const __nv_bfloat16*)d_in[1], (const __nv_bfloat16*)d_in[2],
        (const __nv_bfloat16*)d_in[3], (const __nv_bfloat16*)d_in[4], (const __nv_bfloat16*)d_in[6],
        (const __nv_bfloat16*)d_in[7], (const __nv_bfloat16*)d_in[8], (const __nv_bfloat16*)d_in[9],
        (__nv_bfloat16*)d_out);
}
```

```cpp
#include <cuda_runtime.h>
#include <cuda_bf16.h>
#include <stdint.h>

#define NS 12
#define CAP 3
#define PSTAT 8

#define RING 8
#define WTO 20000
#define EAGER (2 * 132)
#define STAG 150
#define PAD (1 << 20)
#define YCLR (63 - RING)
#define PTAG(bh) (((epoch % 15u) * ((63 + RING) / RING) + (bh) / RING) % 15u + 1u)
static_assert(NS >= 8 && PSTAT - 1 >= CAP && PSTAT <= NS && CAP >= 3, "ring");
constexpr int G = 132;
constexpr int NUNITS = 64 * 512;
constexpr int NDRAW = NUNITS - G * PSTAT + 2 * G;
constexpr int NTHREADS = 448;
constexpr int DF = 1376;
constexpr uint32_t YTAG = 8u;
constexpr int SPIN_LIMIT = 1 << 22;

constexpr int OFF_RING = 0;
constexpr int OFF_Q = NS * 16384;
constexpr int OFF_RES = OFF_Q + 16384;
constexpr int OFF_X = OFF_RES + NS * 528;
constexpr int OFF_RED = OFF_X + 4096;
constexpr int OFF_COEF = OFF_RED + 2048;
constexpr int OFF_CMB = OFF_COEF + 192;
constexpr int OFF_META = OFF_CMB + 576;
constexpr int OFF_BAR = OFF_META + NS * 8;
constexpr int OFF_N = OFF_BAR + (3 * NS + 7) * 8;
constexpr int SMEM_BYTES = OFF_N + 16;
static_assert(SMEM_BYTES <= 232448, "smem");

struct __align__(256) Scratch {
    uint4 y[128 * 128 * 2];
    uint4 po[RING * 4 * G * 8];
    uint32_t q[2 * 4096];
    uint32_t h[2 * DF];
    uint2 pml[RING * G];
    uint4 cons[64];
    unsigned epoch, pad0[63];
    unsigned ctr, pad1[63];
    unsigned char pad2[PAD];
};
__device__ Scratch g_s;
#define g_y g_s.y
#define g_po g_s.po
#define g_q g_s.q
#define g_h g_s.h
#define g_pml g_s.pml
#define g_cons g_s.cons
#define g_epoch g_s.epoch
#define g_ctr g_s.ctr

__device__ __forceinline__ uint32_t s2u(const void* p) { return (uint32_t)__cvta_generic_to_shared(p); }
__device__ __forceinline__ void mbar_init(uint32_t b, int c) { asm volatile("mbarrier.init.shared::cta.b64 [%0], %1;" ::"r"(b), "r"(c) : "memory"); }
__device__ __forceinline__ void mbar_expect(uint32_t b, uint32_t bytes) { asm volatile("mbarrier.arrive.expect_tx.shared::cta.b64 _, [%0], %1;" ::"r"(b), "r"(bytes) : "memory"); }
__device__ __forceinline__ void mbar_expect_only(uint32_t b, uint32_t bytes) { asm volatile("mbarrier.expect_tx.shared::cta.b64 [%0], %1;" ::"r"(b), "r"(bytes) : "memory"); }
__device__ __forceinline__ void mbar_arrive(uint32_t b) { asm volatile("mbarrier.arrive.shared::cta.b64 _, [%0];" ::"r"(b) : "memory"); }
__device__ __forceinline__ void mbar_wait(uint32_t b, uint32_t ph) {
    uint32_t ok;
    int it = 0;
    do {
        asm volatile("{\n.reg .pred p;\nmbarrier.try_wait.parity.shared::cta.b64 p, [%1], %2;\nselp.u32 %0, 1, 0, p;\n}" : "=r"(ok) : "r"(b), "r"(ph) : "memory");
        if (++it > SPIN_LIMIT) __trap();
    } while (!ok);
}
__device__ __forceinline__ bool mbar_test(uint32_t b, uint32_t ph) {
    uint32_t ok;
    asm volatile("{\n.reg .pred p;\nmbarrier.test_wait.parity.shared::cta.b64 p, [%1], %2;\nselp.u32 %0, 1, 0, p;\n}" : "=r"(ok) : "r"(b), "r"(ph) : "memory");
    return ok;
}
__device__ __forceinline__ void bulk(uint32_t dst, const void* src, uint32_t bytes, uint32_t bar, uint64_t pol) {
    asm volatile("cp.async.bulk.shared::cluster.global.mbarrier::complete_tx::bytes.L2::cache_hint [%0], [%1], %2, [%3], %4;" ::"r"(dst), "l"(src), "r"(bytes), "r"(bar), "l"(pol) : "memory");
}
__device__ __forceinline__ uint64_t evict_first() {
    uint64_t pol;
    asm volatile("createpolicy.fractional.L2::evict_first.b64 %0, 1.0;" : "=l"(pol));
    return pol;
}
__device__ __forceinline__ uint4 lds128(uint32_t a) {
    uint4 v;
    asm volatile("ld.shared.v4.u32 {%0,%1,%2,%3}, [%4];" : "=r"(v.x), "=r"(v.y), "=r"(v.z), "=r"(v.w) : "r"(a));
    return v;
}
__device__ __forceinline__ uint4 ldsm4t(uint32_t a) {
    uint4 v;
    asm volatile("ldmatrix.sync.aligned.m8n8.x4.trans.shared.b16 {%0,%1,%2,%3}, [%4];" : "=r"(v.x), "=r"(v.y), "=r"(v.z), "=r"(v.w) : "r"(a));
    return v;
}
__device__ __forceinline__ void mma(float (&c)[4], uint32_t a0, uint32_t a1, uint32_t a2, uint32_t a3, uint32_t b0, uint32_t b1) {
    asm volatile("mma.sync.aligned.m16n8k16.row.col.f32.bf16.bf16.f32 {%0,%1,%2,%3}, {%4,%5,%6,%7}, {%8,%9}, {%0,%1,%2,%3};"
                 : "+f"(c[0]), "+f"(c[1]), "+f"(c[2]), "+f"(c[3]) : "r"(a0), "r"(a1), "r"(a2), "r"(a3), "r"(b0), "r"(b1));
}
__device__ __forceinline__ void mma_top(float (&c)[4], uint32_t a0, uint32_t a2, uint32_t b0, uint32_t b1) {
    asm volatile("{\n.reg .b32 u1, u3;\nmma.sync.aligned.m16n8k16.row.col.f32.bf16.bf16.f32 {%0,%1,%2,%3}, {%4,u1,%5,u3}, {%6,%7}, {%0,%1,%2,%3};\n}"
                 : "+f"(c[0]), "+f"(c[1]), "+f"(c[2]), "+f"(c[3]) : "r"(a0), "r"(a2), "r"(b0), "r"(b1));
}
__device__ __forceinline__ void put_q(unsigned char* q, int i, uint4 v) {
    uint32_t* d = (uint32_t*)(q + (i >> 4) * 128 + (i & 1) * 64 + (i & 6) * 8 + (i & 8) / 2);
    d[0] = __byte_perm(v.x, v.y, 0x7632);
    d[2] = __byte_perm(v.z, v.w, 0x7632);
}
__device__ __forceinline__ uint4 ldg_nc(const void* p) {
    uint4 v;
    asm volatile("ld.global.nc.L1::no_allocate.v4.u32 {%0,%1,%2,%3}, [%4];" : "=r"(v.x), "=r"(v.y), "=r"(v.z), "=r"(v.w) : "l"(p));
    return v;
}
__device__ __forceinline__ uint4 ld_poll4(const void* p) {
    uint4 v;
    asm volatile("ld.relaxed.gpu.global.v4.u32 {%0,%1,%2,%3}, [%4];" : "=r"(v.x), "=r"(v.y), "=r"(v.z), "=r"(v.w) : "l"(p) : "memory");
    return v;
}
__device__ __forceinline__ uint2 ld_poll2(const void* p) {
    uint2 v;
    asm volatile("ld.relaxed.gpu.global.v2.u32 {%0,%1}, [%2];" : "=r"(v.x), "=r"(v.y) : "l"(p) : "memory");
    return v;
}
__device__ __forceinline__ void repoll4(uint4& v, const void* p, uint32_t tag) {
    const uint32_t bad = ((v.x ^ tag) | (v.y ^ tag) | (v.z ^ tag) | (v.w ^ tag)) & 15u;
    asm volatile("{\n.reg .pred p;\nsetp.ne.u32 p, %5, 0;\n@p ld.relaxed.gpu.global.v4.u32 {%0,%1,%2,%3}, [%4];\n}"
                 : "+r"(v.x), "+r"(v.y), "+r"(v.z), "+r"(v.w) : "l"(p), "r"(bad) : "memory");
}
__device__ __forceinline__ void repoll2(uint2& v, const void* p, uint32_t tag) {
    const uint32_t bad = ((v.x ^ tag) | (v.y ^ tag)) & 15u;
    asm volatile("{\n.reg .pred p;\nsetp.ne.u32 p, %3, 0;\n@p ld.relaxed.gpu.global.v2.u32 {%0,%1}, [%2];\n}"
                 : "+r"(v.x), "+r"(v.y) : "l"(p), "r"(bad) : "memory");
}
__device__ __forceinline__ uint32_t ld_poll1(const void* p) {
    uint32_t v;
    asm volatile("ld.relaxed.gpu.global.u32 %0, [%1];" : "=r"(v) : "l"(p) : "memory");
    return v;
}
__device__ __forceinline__ void st_pub4(void* p, uint32_t a, uint32_t b, uint32_t c, uint32_t d) {
    asm volatile("st.relaxed.gpu.global.v4.u32 [%0], {%1,%2,%3,%4};" ::"l"(p), "r"(a), "r"(b), "r"(c), "r"(d) : "memory");
}
__device__ __forceinline__ void st_pub2(void* p, uint32_t a, uint32_t b) {
    asm volatile("st.relaxed.gpu.global.v2.u32 [%0], {%1,%2};" ::"l"(p), "r"(a), "r"(b) : "memory");
}
__device__ __forceinline__ void st_pub1(void* p, uint32_t a) {
    asm volatile("st.relaxed.gpu.global.u32 [%0], %1;" ::"l"(p), "r"(a) : "memory");
}
__device__ __forceinline__ int ticket(unsigned* p) {
    int v;
    asm volatile("atom.relaxed.gpu.global.inc.u32 %0, [%1], %2;" : "=r"(v) : "l"(p), "n"(NDRAW - 1) : "memory");
    return v;
}
__device__ __forceinline__ uint32_t tg(float v, uint32_t tag) { return (__float_as_uint(v) & ~15u) | tag; }
__device__ __forceinline__ float blo(uint32_t v) { return __uint_as_float(v << 16); }
__device__ __forceinline__ float bhi(uint32_t v) { return __uint_as_float(v & 0xffff0000u); }
__device__ __forceinline__ float ex2(float x) { float r; asm("ex2.approx.ftz.f32 %0, %1;" : "=f"(r) : "f"(x)); return r; }
__device__ __forceinline__ uint32_t packbf(float lo, float hi) {
    uint32_t r;
    asm("cvt.rn.bf16x2.f32 %0, %1, %2;" : "=r"(r) : "f"(hi), "f"(lo));
    return r;
}
__device__ __forceinline__ void fma8(float (&a)[8], uint4 w, float x) {
    a[0] = fmaf(blo(w.x), x, a[0]); a[1] = fmaf(bhi(w.x), x, a[1]);
    a[2] = fmaf(blo(w.y), x, a[2]); a[3] = fmaf(bhi(w.y), x, a[3]);
    a[4] = fmaf(blo(w.z), x, a[4]); a[5] = fmaf(bhi(w.z), x, a[5]);
    a[6] = fmaf(blo(w.w), x, a[6]); a[7] = fmaf(bhi(w.w), x, a[7]);
}
__device__ __forceinline__ void spin(int cyc) { const uint32_t c0 = clock(); while ((uint32_t)clock() - c0 < (uint32_t)cyc) {} }
__device__ __forceinline__ void cbar() { asm volatile("bar.sync 1, 256;" ::: "memory"); }

__global__ void __launch_bounds__(NTHREADS, 1)
fused_decode_kernel(const __nv_bfloat16* __restrict__ x, const __nv_bfloat16* __restrict__ Kc, const __nv_bfloat16* __restrict__ Vc,
                    const __nv_bfloat16* __restrict__ wq, const __nv_bfloat16* __restrict__ wo,
                    const __nv_bfloat16* __restrict__ wg, const __nv_bfloat16* __restrict__ wu,
                    const __nv_bfloat16* __restrict__ wd, const __nv_bfloat16* __restrict__ gw,
                    __nv_bfloat16* __restrict__ out) {
    extern __shared__ __align__(1024) unsigned char smem[];
    const int tid = threadIdx.x, lane = tid & 31, warp = tid >> 5, cta = blockIdx.x;
    const uint32_t sb = s2u(smem);
    const uint32_t bFull = sb + OFF_BAR, bDone = bFull + NS * 8, bEmpty = bDone + NS * 8, bW = bEmpty + NS * 8,
                   bHfin = bW + 8, bNop = bW + 16, bCb = bW + 24, bOfin = bCb + 16, bQ = bOfin + 8;
    float* xs = (float*)(smem + OFF_X);
    volatile int2* meta = (volatile int2*)(smem + OFF_META);
    const int r0 = (cta * 43) >> 2, nr = (((cta + 1) * 43) >> 2) - r0;

    uint4 wreg[8];
    int pw;
    asm volatile("shr.u32 %0, %1, 5;" : "=r"(pw) : "r"(tid));
    if (pw == 8) {
        if (lane == 0) {
#pragma unroll
            for (int i = 0; i < 3 * NS + 7; i++) mbar_init(bFull + i * 8, (i == 3 * NS + 6 || i == 3 * NS + 1) ? 2 : 1);
            asm volatile("fence.mbarrier_init.release.cluster;" ::: "memory");
        }
        __syncwarp();
        asm volatile("bar.arrive 3, %0;" ::"n"(NTHREADS) : "memory");
    } else if (warp < 8) {
        if (cta < 128) {
            const __nv_bfloat16* p = wq + (size_t)(tid >> 2) * 8 * 4096 + cta * 32 + (tid & 3) * 8;
#pragma unroll
            for (int i = 0; i < 8; i++) wreg[i] = ldg_nc(p + (size_t)i * 4096);
        }
    } else if (pw >= 10) {
        wreg[0] = ldg_nc(x + (tid - 320) * 8);
        wreg[1].x = ld_poll1(&g_epoch);
    }
    if (warp != 8) asm volatile("bar.sync 3, %0;" ::"n"(NTHREADS) : "memory");

    if (warp == 8) {
        if (lane == 0) {
            const uint64_t pol = evict_first();
            int ta = cta - G * PSTAT, tb = ta + G, tc;
            int st = 0, cst = NS - CAP;
            uint32_t eph = 1, cph = 1;
            const __nv_bfloat16 *Kp = Kc + (size_t)G * PSTAT * 4096, *Vp = Vc + (size_t)G * PSTAT * 4096;
#define STEP(cur, nxt, nn)                                                                   \
            if (cur >= NUNITS - G * PSTAT) break;                                            \
            if (cur < -2 * G) nn = cur + 2 * G; else nn = ticket(&g_ctr);                    \
            if (cur < NUNITS - G * PSTAT - EAGER) mbar_wait(bFull + cst * 8, cph);           \
            mbar_wait(bEmpty + st * 8, eph);                                                 \
            mbar_expect_only(bFull + st * 8, 16384);                                         \
            bulk(sb + st * 16384, Kp + (ptrdiff_t)cur * 4096, 8192, bFull + st * 8, pol);    \
            bulk(sb + st * 16384 + 8192, Vp + (ptrdiff_t)cur * 4096, 8192, bFull + st * 8, pol); \
            meta[st].x = cur + G * PSTAT; meta[st].y = nxt + G * PSTAT;                      \
            mbar_arrive(bFull + st * 8);                                                     \
            if (++st == NS) { st = 0; eph ^= 1; }                                            \
            if (++cst == NS) { cst = 0; cph ^= 1; }
            while (true) {
                STEP(ta, tb, tc)
                STEP(tb, tc, ta)
                STEP(tc, ta, tb)
            }
#undef STEP
            const uint32_t tend = clock();
            *(volatile int*)(smem + OFF_N) = st;
            const int last = st == 0 ? NS - 1 : st - 1;
            const uint32_t lph = st == 0 ? eph : eph ^ 1;
            int wsl = st;
#pragma unroll 1
            for (int i = 0; i < 8; i++) {
                mbar_wait(bEmpty + st * 8, eph);
                meta[st].x = -1;
                mbar_arrive(bFull + st * 8);
                if (++st == NS) { st = 0; eph ^= 1; }
                if (i == 2 && cta < 128) {
                    mbar_expect(bW, nr * 1024 + 32768);
                    const __nv_bfloat16* src = wd + (size_t)r0 * 512;
                    uint32_t bytes = nr * 1024;
                    while (!mbar_test(bFull + last * 8, lph) && (uint32_t)clock() - tend < WTO) {}
#pragma unroll 1
                    for (int j = 0; j < 3; j++) {
                        bulk(sb + wsl * 16384, src, bytes, bW, pol);
                        src = wo + (size_t)(cta * 32 + j * 16) * 512;
                        bytes = 16384;
                        if (++wsl == NS) wsl = 0;
                    }
                }
            }
        }
    } else if (warp == 9) {
        const unsigned epoch = ld_poll1(&g_epoch);
        float m = -1e30f, l = 0.f, o0 = 0.f, o1 = 0.f, o2 = 0.f, o3 = 0.f;
        int st = 0; uint32_t ph = 0;
        const int myh = cta >> 2;
        uint4 cons = make_uint4(0u, 0u, 0u, 0u);
        bool live = false;
        while (true) {
            mbar_wait(live ? bDone + st * 8 : bOfin, live ? ph : 1u);
            const int u = live ? meta[st].x : 0, nx = live ? meta[st].y : 0;
            const float* res = (const float*)(smem + OFF_RES + st * 528);
            const float4 v = *(const float4*)(res + lane * 4);
            const float2 ml = *(const float2*)(res + 128);
            __syncwarp();
            if (lane == 0) mbar_arrive(live ? bEmpty + st * 8 : bNop);
            const float mn = fmaxf(m, ml.x);
            const float a = ex2(m - mn), b = ex2(ml.x - mn);
            m = mn;
            l = l * a + ml.y * b;
            o0 = o0 * a + v.x * b; o1 = o1 * a + v.y * b; o2 = o2 * a + v.z * b; o3 = o3 * a + v.w * b;
            const int nb = min(nx >> 9, 64);
            for (int bh = u >> 9; bh < nb; bh++) {
                const uint32_t ptag = PTAG(bh);
                if (bh >= RING) {
                    int it = 0;
                    while (cons.x != epoch + 1 || cons.y != epoch + 1 || cons.z != epoch + 1 || cons.w != epoch + 1) {
                        cons = ld_poll4(&g_cons[bh - RING]);
                        if (++it > SPIN_LIMIT) __trap();
                    }
                }
                if (bh == YCLR && cta < 128) {
#pragma unroll
                    for (int i = 0; i < 8; i++) st_pub4(&g_y[cta * 256 + i * 32 + lane], 0u, 0u, 0u, 0u);
                    __threadfence();
                    __syncwarp();
                }
                st_pub4(&g_po[(((bh % RING) * 4 + (lane >> 3)) * G + cta) * 8 + (lane & 7)], tg(o0, ptag), tg(o1, ptag), tg(o2, ptag), tg(o3, ptag));
                if (lane == 0) {
                    st_pub2(&g_pml[(bh % RING) * G + cta], tg(m, ptag), tg(l, ptag));
                    if ((bh & 31) == myh) mbar_arrive(bCb + (bh >> 5) * 8);
                }
                if (bh + 1 >= RING && bh < 63) cons = ld_poll4(&g_cons[bh + 1 - RING]);
                m = -1e30f; l = 0.f; o0 = o1 = o2 = o3 = 0.f;
            }
            if (nb == 64) { if (lane == 0) mbar_arrive(bHfin); break; }
            if (!live) { live = true; m = -1e30f; l = 0.f; o0 = o1 = o2 = o3 = 0.f; continue; }
            if (++st == NS) { st = 0; ph ^= 1; }
        }
    } else if (warp >= 10) {
        const int cw = warp - 10;
        const uint4 xr0 = wreg[0];
        const unsigned epoch = wreg[1].x;
        const uint32_t tag = epoch % 15u + 1u;
        {
            if (tid == 320) *(volatile uint32_t*)(smem + OFF_N + 4) = tag;
            float4* d = (float4*)(xs + (tid - 320) * 8);
            d[0] = make_float4(blo(xr0.x), bhi(xr0.x), blo(xr0.y), bhi(xr0.y));
            d[1] = make_float4(blo(xr0.z), bhi(xr0.z), blo(xr0.w), bhi(xr0.w));
            asm volatile("bar.arrive 4, 384;" ::: "memory");
            asm volatile("bar.sync 2, 128;" ::: "memory");
        }
        if (cw >= 2) {
            asm volatile("bar.sync 5, 320;" ::: "memory");
#pragma unroll 1
            for (int j = 0; j < 4; j++) {
                uint4 v[7];
                const int i0 = 256 + j * 448 + tid - 384;
                int it = 0;
                while (true) {
                    uint32_t bad = 0;
#pragma unroll
                    for (int i = 0; i < 7; i++) v[i] = ld_poll4((const uint4*)g_q + i0 + i * 64);
#pragma unroll
                    for (int i = 0; i < 7; i++) bad |= (v[i].x ^ tag) | (v[i].y ^ tag) | (v[i].z ^ tag) | (v[i].w ^ tag);
                    if ((bad & 0xffffu) == 0) break;
                    if (++it > SPIN_LIMIT) __trap();
                    __nanosleep(200);
                }
#pragma unroll
                for (int i = 0; i < 7; i++)
                    put_q(smem + OFF_Q, i0 + i * 64, v[i]);
            }
            __syncwarp();
            if (lane == 0) mbar_arrive(bQ);
        }
        if (cta >= G - 11) {
            const int f0 = min((cta - (G - 11)) * 128 + (lane & 15) * 8, DF - 8), b = lane >> 4;
            float ag[2][8], au[2][8];
#pragma unroll
            for (int i = 0; i < 8; i++) ag[0][i] = ag[1][i] = au[0][i] = au[1][i] = 0.f;
            const size_t off = (size_t)(cw * 128 + b) * DF + f0;
#pragma unroll 1
            for (int it = 0; it < 8; it++) {
                uint4 wa[8], wb[8];
#pragma unroll
                for (int i = 0; i < 8; i++) {
                    wa[i] = ldg_nc(wg + off + (size_t)(it * 16 + i * 2) * DF);
                    wb[i] = ldg_nc(wu + off + (size_t)(it * 16 + i * 2) * DF);
                }
#pragma unroll
                for (int i = 0; i < 8; i++) {
                    const int r = cw * 128 + it * 16 + i * 2 + b;
                    const float x0 = xs[r], x1 = xs[512 + r];
                    fma8(ag[0], wa[i], x0); fma8(ag[1], wa[i], x1);
                    fma8(au[0], wb[i], x0); fma8(au[1], wb[i], x1);
                }
            }
            float gv[8], uv[8];
#pragma unroll
            for (int i = 0; i < 8; i++) {
                gv[i] = (b ? ag[1][i] : ag[0][i]) + __shfl_xor_sync(~0u, b ? ag[0][i] : ag[1][i], 16);
                uv[i] = (b ? au[1][i] : au[0][i]) + __shfl_xor_sync(~0u, b ? au[0][i] : au[1][i], 16);
            }
            float* acc = (float*)(smem + OFF_RED) + lane;
#pragma unroll 1
            for (int k = 0; k < 4; k++) {
                if (((cw + 2) & 3) == k) {
#pragma unroll
                    for (int i = 0; i < 8; i++) {
                        if (k > 0) { gv[i] += acc[i * 64]; uv[i] += acc[i * 64 + 32]; }
                        acc[i * 64] = gv[i]; acc[i * 64 + 32] = uv[i];
                    }
                }
                asm volatile("bar.sync 2, 128;" ::: "memory");
            }
            if (cw == 1) {
                uint32_t hv[8];
#pragma unroll
                for (int i = 0; i < 8; i++) {
                    const float t = tanhf(0.7978845608028654f * (gv[i] + 0.044715f * gv[i] * gv[i] * gv[i]));
                    hv[i] = tg(0.5f * gv[i] * (1.f + t) * uv[i], tag);
                }
                uint32_t* d = &g_h[b * DF + f0];
                st_pub4(d, hv[0], hv[1], hv[2], hv[3]);
                st_pub4(d + 4, hv[4], hv[5], hv[6], hv[7]);
            }
        }
        if (cta < 128) {
            __nv_bfloat16* coef = (__nv_bfloat16*)(smem + OFF_COEF);
            float* cmb = (float*)(smem + OFF_CMB);
            float gate0 = 0.f, gate1 = 0.f;
            if (cw == 0) {
                const uint4 w0 = ldg_nc(gw + lane * 16), w1 = ldg_nc(gw + lane * 16 + 8);
                const uint32_t w[8] = {w0.x, w0.y, w0.z, w0.w, w1.x, w1.y, w1.z, w1.w};
#pragma unroll
                for (int i = 0; i < 8; i++) {
                    gate0 = fmaf(blo(w[i]), xs[lane * 16 + 2 * i], gate0);
                    gate0 = fmaf(bhi(w[i]), xs[lane * 16 + 2 * i + 1], gate0);
                    gate1 = fmaf(blo(w[i]), xs[512 + lane * 16 + 2 * i], gate1);
                    gate1 = fmaf(bhi(w[i]), xs[512 + lane * 16 + 2 * i + 1], gate1);
                }
#pragma unroll
                for (int k = 1; k < 32; k <<= 1) {
                    gate0 += __shfl_xor_sync(~0u, gate0, k);
                    gate1 += __shfl_xor_sync(~0u, gate1, k);
                }
                gate0 = 1.f / (1.f + __expf(-gate0));
                gate1 = 1.f / (1.f + __expf(-gate1));
            }
#pragma unroll 1
            for (int b = 0; b < 2; b++) {
                const int bh = b * 32 + (cta >> 2);
                if (b == 1 && cw == 0) {
                    const int r = lane & 15, bb = lane >> 4;
                    uint32_t hv = tag;
                    if (r < nr) {
                        int it = 0;
                        do {
                            hv = ld_poll1(&g_h[bb * DF + r0 + r]);
                            if (++it > SPIN_LIMIT) __trap();
                            if ((hv & 15u) != tag) __nanosleep(1000);
                        } while ((hv & 15u) != tag);
                    }
                    coef[bb * 48 + r] = __float2bfloat16(r < nr ? __uint_as_float(hv) * (1.f - (bb ? gate1 : gate0)) : 0.f);
                    __syncwarp();
                    if (lane == 0) mbar_arrive(bHfin);
                }
                mbar_wait(bCb + b * 8, 0);
                const uint4* po = &g_po[((bh % RING) * 4 + (cta & 3)) * G * 8];
                const uint2* pm = &g_pml[(bh % RING) * G];
                const uint32_t ptag = PTAG(bh);
                uint4 v[9];
                uint2 ml = make_uint2(0u, 0u), mle = ml;
#pragma unroll
                for (int i = 0; i < 9; i++) v[i] = make_uint4(0u, 0u, 0u, 0u);
                int it = 0;
                while (true) {
                    repoll2(ml, pm + cw * 32 + lane, ptag);
                    repoll2(mle, pm + 128 + cw, ptag);
#pragma unroll
                    for (int i = 0; i < 8; i++) repoll4(v[i], po + cw * 256 + i * 32 + lane, ptag);
                    repoll4(v[8], po + (128 + cw) * 8 + (lane & 7), ptag);
                    uint32_t bad = (v[8].x ^ ptag) | (v[8].y ^ ptag) | (v[8].z ^ ptag) | (v[8].w ^ ptag);
#pragma unroll
                    for (int i = 7; i >= 0; i--) bad |= (v[i].x ^ ptag) | (v[i].y ^ ptag) | (v[i].z ^ ptag) | (v[i].w ^ ptag);
                    bad |= (ml.x ^ ptag) | (ml.y ^ ptag) | (mle.x ^ ptag) | (mle.y ^ ptag);
                    const bool ok = !__any_sync(~0u, (bad & 15u) != 0);
                    if (ok) {
                        int key = __float_as_int(fmaxf(__uint_as_float(ml.x), __uint_as_float(mle.x)));
                        key = __reduce_max_sync(~0u, key ^ ((key >> 31) & 0x7fffffff));
                        const float M = __int_as_float(key ^ ((key >> 31) & 0x7fffffff));
                        const float w = ex2(__uint_as_float(ml.x) - M), wl = w * __uint_as_float(ml.y & ~15u);
                        const float we = lane < 8 ? ex2(__uint_as_float(mle.x) - M) : 0.f;
                        float L = we * __uint_as_float(mle.y & ~15u);
                        float o0 = we * __uint_as_float(v[8].x), o1 = we * __uint_as_float(v[8].y), o2 = we * __uint_as_float(v[8].z), o3 = we * __uint_as_float(v[8].w);
#pragma unroll
                        for (int i = 0; i < 8; i++) {
                            const float wi = __shfl_sync(~0u, w, 4 * i + (lane >> 3));
                            L += __shfl_sync(~0u, wl, 4 * i + (lane >> 3));
                            o0 = fmaf(wi, __uint_as_float(v[i].x), o0); o1 = fmaf(wi, __uint_as_float(v[i].y), o1);
                            o2 = fmaf(wi, __uint_as_float(v[i].z), o2); o3 = fmaf(wi, __uint_as_float(v[i].w), o3);
                        }
#pragma unroll
                        for (int k = 8; k < 32; k <<= 1) {
                            o0 += __shfl_xor_sync(~0u, o0, k); o1 += __shfl_xor_sync(~0u, o1, k);
                            o2 += __shfl_xor_sync(~0u, o2, k); o3 += __shfl_xor_sync(~0u, o3, k);
                            L += __shfl_xor_sync(~0u, L, k);
                        }
                        if (lane < 8) *(float4*)(cmb + cw * 36 + lane * 4) = make_float4(o0, o1, o2, o3);
                        if (lane == 8) *(float2*)(cmb + cw * 36 + 32) = make_float2(M, L);
                    }
                    if (ok) break;
                    if (++it > SPIN_LIMIT) __trap();
                }
                __syncwarp();
                asm volatile("bar.sync 2, 128;" ::: "memory");
                if (cw == 0) {
                    {
                        const float2 a0 = *(const float2*)(cmb + 32), a1 = *(const float2*)(cmb + 68), a2 = *(const float2*)(cmb + 104), a3 = *(const float2*)(cmb + 140);
                        const float MM = fmaxf(fmaxf(a0.x, a1.x), fmaxf(a2.x, a3.x));
                        const float e0 = ex2(a0.x - MM), e1 = ex2(a1.x - MM), e2 = ex2(a2.x - MM), e3 = ex2(a3.x - MM);
                        const float LL = (e0 * a0.y + e1 * a1.y) + (e2 * a2.y + e3 * a3.y);
                        const float o = (e0 * cmb[lane] + e1 * cmb[36 + lane]) + (e2 * cmb[72 + lane] + e3 * cmb[108 + lane]);
                        coef[b * 48 + 16 + lane] = __float2bfloat16(o * __fdividef(b ? gate1 : gate0, LL));
                        __syncwarp();
                        if (b == 1 && lane == 0) mbar_arrive(bOfin);
                    }
                    if (lane == 0) st_pub1((uint32_t*)&g_cons[bh] + (cta & 3), epoch + 1);
                    if (lane == 0 && b == 1 && cta == 127) g_epoch = epoch + 1;
                }
                if (b == 0) asm volatile("bar.sync 2, 128;" ::: "memory");
            }
        }
    } else {
        float* red = (float*)(smem + OFF_RED);
        const int g = lane >> 2, t = lane & 3;
        const uint32_t kE = g * 256 + t * 16 + (g & 1) * 64, kO = g * 256 + t * 16 + 64 - (g & 1) * 64;
        uint32_t voff[8], msk[8];
        {
            const int mi = lane >> 3, i = lane & 7;
            const uint32_t vb = 8192 + (8 * (mi & 1) + i) * 256 + 128 * (mi >> 1);
#pragma unroll
            for (int c = 0; c < 8; c++) {
                voff[c] = vb + ((c + i) & 7) * 16;
                msk[c] = (((c + 2 * t) & 7) == g ? 0x0000ffffu : 0u) | (((c + 2 * t + 1) & 7) == g ? 0xffff0000u : 0u);
            }
        }
        const float SC = 0.08838834764831845f * 1.4426950408889634f;
        int st = warp, qlim = 8 * 512; uint32_t ph = 0;
#pragma unroll 1
        for (int pass = 0; pass < 2; pass++) {
        if (pass) {
        asm volatile("bar.sync 4, 384;" ::: "memory");
        const uint32_t tag = *(volatile uint32_t*)(smem + OFF_N + 4);
        if (cta < 128) {
            float a0[8], a1[8];
#pragma unroll
            for (int i = 0; i < 8; i++) a0[i] = a1[i] = 0.f;
#pragma unroll
            for (int i = 0; i < 8; i++) {
                asm volatile("" : "+r"(wreg[i].x), "+r"(wreg[i].y), "+r"(wreg[i].z), "+r"(wreg[i].w));
                fma8(a0, wreg[i], xs[(tid >> 2) * 8 + i]);
                fma8(a1, wreg[i], xs[512 + (tid >> 2) * 8 + i]);
            }
#pragma unroll
            for (int i = 0; i < 8; i++)
#pragma unroll
                for (int s = 4; s < 32; s <<= 1) {
                    a0[i] += __shfl_xor_sync(~0u, a0[i], s);
                    a1[i] += __shfl_xor_sync(~0u, a1[i], s);
                }
            if (lane < 8) {
                float4* d = (float4*)(red + warp * 64 + lane * 8);
                if (lane < 4) { d[0] = make_float4(a0[0], a0[1], a0[2], a0[3]); d[1] = make_float4(a0[4], a0[5], a0[6], a0[7]); }
                else          { d[0] = make_float4(a1[0], a1[1], a1[2], a1[3]); d[1] = make_float4(a1[4], a1[5], a1[6], a1[7]); }
            }
            cbar();
            if (tid < 64) {
                float s = 0.f;
#pragma unroll
                for (int w = 0; w < 8; w++) s += red[w * 64 + tid];
                st_pub1(&g_q[(tid >> 5) * 4096 + cta * 32 + (tid & 31)], (packbf(0.f, s) & 0xffff0000u) | tag);
            }
        }
            uint4 v;
            int it = 0;
            do {
                v = ld_poll4((const uint4*)g_q + tid);
                if (++it > SPIN_LIMIT) __trap();
            } while ((((v.x ^ tag) | (v.y ^ tag) | (v.z ^ tag) | (v.w ^ tag)) & 0xffffu) != 0);
            put_q(smem + OFF_Q, tid, v);
            asm volatile("bar.sync 5, 320;" ::: "memory");
        }

        while (true) {
            mbar_wait(bDone + st * 8, ph ^ 1);
            mbar_wait((pass ? bFull : bDone) + st * 8, pass ? ph : 1u);
            const int u = pass ? meta[st].x : 0;
            if (u < 0) break;
            if (u >= qlim) { mbar_wait(bQ, 0); qlim = NUNITS; }
            const uint32_t base = sb + st * 16384;
            const uint32_t qa = sb + OFF_Q + (u >> 9) * 256 + t * 16;
            uint4 Q[4];
#pragma unroll
            for (int j = 0; j < 4; j++) Q[j] = lds128(qa + j * 64);
            float s[2][4][4];
#pragma unroll
            for (int n = 0; n < 8; n++) s[n >> 2][n & 3][0] = s[n >> 2][n & 3][1] = s[n >> 2][n & 3][2] = s[n >> 2][n & 3][3] = 0.f;
#pragma unroll
            for (int j = 0; j < 4; j++) {
#pragma unroll
                for (int n = 0; n < 4; n++) {
                    const uint4 kk = lds128(base + n * 2048 + ((j & 1) ? kO : kE) + (j >> 1) * 128);
                    mma(s[j & 1][n], Q[j & 2].x, Q[j & 2].y, Q[j & 2].z, Q[j & 2].w, kk.x, kk.y);
                    mma(s[j & 1][n], Q[j | 1].x, Q[j | 1].y, Q[j | 1].z, Q[j | 1].w, kk.z, kk.w);
                }
            }
            float sa[4], sc[4];
#pragma unroll
            for (int n = 0; n < 4; n++) { sa[n] = s[0][n][0] + s[1][n][2]; sc[n] = s[0][n][3] + s[1][n][1]; }
            float mx = fmaxf(fmaxf(fmaxf(sa[0], sc[0]), fmaxf(sa[1], sc[1])), fmaxf(fmaxf(sa[2], sc[2]), fmaxf(sa[3], sc[3])));
            mx = fmaxf(mx, __shfl_xor_sync(~0u, mx, 1));
            mx = fmaxf(mx, __shfl_xor_sync(~0u, mx, 2));
            const float mu = mx * SC;
            uint32_t P[4];
            float l = 0.f;
#pragma unroll
            for (int n = 0; n < 4; n++) {
                const float p0 = ex2(fmaf(sa[n], SC, -mu)), p1 = ex2(fmaf(sc[n], SC, -mu));
                l += p0 + p1;
                P[n] = packbf(p0, p1);
            }
            l += __shfl_xor_sync(~0u, l, 1);
            l += __shfl_xor_sync(~0u, l, 2);
            float o[4][4];
#pragma unroll
            for (int n = 0; n < 4; n++) o[n][0] = o[n][1] = o[n][2] = o[n][3] = 0.f;
#pragma unroll
            for (int c = 0; c < 8; c++) {
#pragma unroll
                for (int T = 0; T < 2; T++) {
                    const uint4 vv = ldsm4t(base + voff[c] + T * 4096);
                    const uint32_t pl = P[2 * T] & msk[c], phh = P[2 * T + 1] & msk[c];
                    mma_top(o[2 * T], pl, phh, vv.x, vv.y);
                    mma_top(o[2 * T + 1], pl, phh, vv.z, vv.w);
                }
            }
            float* res = (float*)(smem + OFF_RES + st * 528);
            *(float2*)(res + 2 * lane) = make_float2(o[0][0] + o[2][0], o[0][1] + o[2][1]);
            *(float2*)(res + 64 + 2 * lane) = make_float2(o[1][0] + o[3][0], o[1][1] + o[3][1]);
            if (lane == 0) *(float2*)(res + 128) = make_float2(mu, l);
            __syncwarp();
            if (lane == 0) mbar_arrive(pass ? bDone + st * 8 : bNop);
            if (!pass) break;
            st += 8;
            if (st >= NS) { st -= NS; ph ^= 1; }
        }
        }
#pragma unroll 1
        for (int pass = mbar_test(bW, 0) ? 1 : 0; pass < 2; pass++) {
        if (cta < 128) {
            const int s0 = pass ? *(volatile int*)(smem + OFF_N) : 0;
            const uint32_t* coef = (const uint32_t*)(smem + OFF_COEF);
            float y[4][4];
#pragma unroll
            for (int i = 0; i < 4; i++) y[i][0] = y[i][1] = y[i][2] = y[i][3] = 0.f;
            const int mi = lane >> 3, wrow = 8 * (mi & 1) + (lane & 7);
            if (pass) { mbar_wait(bW, 0); mbar_wait(bHfin, 0); }
            uint4 vv[3][4];
#pragma unroll
            for (int i = 0; i < 3; i++) {
                int sl = s0 + i; if (sl >= NS) sl -= NS;
                const uint32_t wb = (pass ? sb + sl * 16384 + (i == 0 ? min(wrow, nr - 1) : wrow) * 1024 : sb + OFF_Q) + warp * 128;
#pragma unroll
                for (int c = 0; c < 4; c++) vv[i][c] = ldsm4t(wb + ((2 * c + (mi >> 1) + lane) & 7) * 16);
            }
            uint32_t cf[3][4];
#pragma unroll
            for (int i = 0; i < 3; i++) { cf[i][0] = coef[i * 8 + t]; cf[i][2] = coef[i * 8 + 4 + t]; }
            cf[0][1] = coef[24 + t]; cf[0][3] = coef[28 + t];
#pragma unroll
            for (int i = 0; i < 3; i++) {
                if (i == 1) {
                    if (pass) mbar_wait(bOfin, 0);
                    cf[1][1] = coef[32 + t]; cf[1][3] = coef[36 + t]; cf[2][1] = coef[40 + t]; cf[2][3] = coef[44 + t];
                }
#pragma unroll
                for (int c = 0; c < 8; c += 2) {
                    mma(y[c & 2], cf[i][0] & msk[c], cf[i][1] & msk[c], cf[i][2] & msk[c], cf[i][3] & msk[c], vv[i][c >> 1].x, vv[i][c >> 1].y);
                    mma(y[(c & 2) + 1], cf[i][0] & msk[c + 1], cf[i][1] & msk[c + 1], cf[i][2] & msk[c + 1], cf[i][3] & msk[c + 1], vv[i][c >> 1].z, vv[i][c >> 1].w);
                }
            }
            uint2* yp = (uint2*)g_y;
            uint4 v;
            if (pass) {
                st_pub2(yp + (((64 + (tid >> 2)) * 128 + cta) * 4 + (tid & 3)), tg((y[0][2] + y[1][2]) + (y[2][2] + y[3][2]), YTAG), tg((y[0][3] + y[1][3]) + (y[2][3] + y[3][3]), YTAG));
                st_pub2(yp + (((tid >> 2) * 128 + cta) * 4 + (tid & 3)), tg((y[0][0] + y[1][0]) + (y[2][0] + y[3][0]), YTAG), tg((y[0][1] + y[1][1]) + (y[2][1] + y[3][1]), YTAG));
            }
            int it = 0;
            {
                const uint4* src = &g_y[cta * 256 + tid];
#define YOK(q) __all_sync(~0u, (((q.x & q.y) & (q.z & q.w)) & YTAG) != 0)
                uint4 p0 = make_uint4(YTAG, YTAG, YTAG, YTAG), p1 = p0, p2 = p0;
                if (pass) {
                    p0 = ld_poll4(src);
                    spin(STAG);
                    p1 = ld_poll4(src);
                    spin(STAG);
                }
                while (true) {
                    if (pass) p2 = ld_poll4(src);
                    if (YOK(p0)) { v = p0; break; }
                    p0 = ld_poll4(src);
                    if (YOK(p1)) { v = p1; break; }
                    p1 = ld_poll4(src);
                    if (YOK(p2)) { v = p2; break; }
                    if (++it > SPIN_LIMIT) __trap();
                }
#undef YOK
            }
            float f0 = __uint_as_float(v.x), f1 = __uint_as_float(v.y), f2 = __uint_as_float(v.z), f3 = __uint_as_float(v.w);
            {
                const bool hi = lane & 2;
                const float s0_ = hi ? f0 : f2, s1_ = hi ? f1 : f3;
                f0 = (hi ? f2 : f0) + __shfl_xor_sync(~0u, s0_, 2);
                f1 = (hi ? f3 : f1) + __shfl_xor_sync(~0u, s1_, 2);
                const bool h2 = lane & 4;
                f0 = (h2 ? f1 : f0) + __shfl_xor_sync(~0u, h2 ? f0 : f1, 4);
                f0 += __shfl_xor_sync(~0u, f0, 8);
                f0 += __shfl_xor_sync(~0u, f0, 16);
            }
            if (lane < 8 && pass) red[warp * 8 + (lane & 1) * 4 + (lane & 2) + (lane >> 2)] = f0;
            if (pass) cbar();
            if (tid < 8) {
                float s = 0.f;
#pragma unroll
                for (int w = 0; w < 8; w++) s += red[w * 8 + tid];
                if (pass) out[cta * 8 + tid] = __float2bfloat16(s);
            }
        }
        }
    }
}

extern "C" void kernel_launch(void* const* d_in, const int* in_sizes, int n_in, void* d_out, int out_size) {
    (void)in_sizes; (void)n_in; (void)out_size;
    cudaFuncSetAttribute(fused_decode_kernel, cudaFuncAttributeMaxDynamicSharedMemorySize, SMEM_BYTES);
    fused_decode_kernel<<<G, NTHREADS, SMEM_BYTES, cudaStreamPerThread>>>(
        (const __nv_bfloat16*)d_in[0], (const __nv_bfloat16*)d_in[1], (const __nv_bfloat16*)d_in[2],
        (const __nv_bfloat16*)d_in[3], (const __nv_bfloat16*)d_in[4], (const __nv_bfloat16*)d_in[6],
        (const __nv_bfloat16*)d_in[7], (const __nv_bfloat16*)d_in[8], (const __nv_bfloat16*)d_in[9],
        (__nv_bfloat16*)d_out);
}
```

```cpp
#include <cuda_runtime.h>
#include <cuda_bf16.h>
#include <stdint.h>

#define NS 12
#define CAP 3
#define PSTAT 8

#define RING 8
#define WTO 20000
#define EAGER (2 * 132)
#define STAG 150
#define PAD (1 << 20)
#define PRE 256
#define MID 256
#define YCLR (63 - RING)
#define PTAG(bh) (((epoch % 15u) * ((63 + RING) / RING) + (bh) / RING) % 15u + 1u)
static_assert(NS >= 8 && PSTAT - 1 >= CAP && PSTAT <= NS && CAP >= 3, "ring");
constexpr int G = 132;
constexpr int NUNITS = 64 * 512;
constexpr int NDRAW = NUNITS - G * PSTAT + 2 * G;
constexpr int NTHREADS = 448;
constexpr int DF = 1376;
constexpr uint32_t YTAG = 8u;
constexpr int SPIN_LIMIT = 1 << 22;

constexpr int OFF_RING = 0;
constexpr int OFF_Q = NS * 16384;
constexpr int OFF_RES = OFF_Q + 16384;
constexpr int OFF_X = OFF_RES + NS * 528;
constexpr int OFF_RED = OFF_X + 4096;
constexpr int OFF_COEF = OFF_RED + 2048;
constexpr int OFF_CMB = OFF_COEF + 192;
constexpr int OFF_META = OFF_CMB + 576;
constexpr int OFF_BAR = OFF_META + NS * 8;
constexpr int OFF_N = OFF_BAR + (3 * NS + 7) * 8;
constexpr int SMEM_BYTES = OFF_N + 16;
static_assert(SMEM_BYTES <= 232448, "smem");

struct __align__(256) Scratch {
    unsigned char pre[PRE];
    uint4 y[128 * 128 * 2];
    unsigned char mid[MID];
    uint4 po[RING * 4 * G * 8];
    uint32_t q[2 * 4096];
    uint32_t h[2 * DF];
    uint2 pml[RING * G];
    uint4 cons[64];
    unsigned epoch, pad0[63];
    unsigned ctr, pad1[63];
    unsigned char pad2[PAD];
};
__device__ Scratch g_s;
#define g_y g_s.y
#define g_po g_s.po
#define g_q g_s.q
#define g_h g_s.h
#define g_pml g_s.pml
#define g_cons g_s.cons
#define g_epoch g_s.epoch
#define g_ctr g_s.ctr

__device__ __forceinline__ uint32_t s2u(const void* p) { return (uint32_t)__cvta_generic_to_shared(p); }
__device__ __forceinline__ void mbar_init(uint32_t b, int c) { asm volatile("mbarrier.init.shared::cta.b64 [%0], %1;" ::"r"(b), "r"(c) : "memory"); }
__device__ __forceinline__ void mbar_expect(uint32_t b, uint32_t bytes) { asm volatile("mbarrier.arrive.expect_tx.shared::cta.b64 _, [%0], %1;" ::"r"(b), "r"(bytes) : "memory"); }
__device__ __forceinline__ void mbar_expect_only(uint32_t b, uint32_t bytes) { asm volatile("mbarrier.expect_tx.shared::cta.b64 [%0], %1;" ::"r"(b), "r"(bytes) : "memory"); }
__device__ __forceinline__ void mbar_arrive(uint32_t b) { asm volatile("mbarrier.arrive.shared::cta.b64 _, [%0];" ::"r"(b) : "memory"); }
__device__ __forceinline__ void mbar_wait(uint32_t b, uint32_t ph) {
    uint32_t ok;
    int it = 0;
    do {
        asm volatile("{\n.reg .pred p;\nmbarrier.try_wait.parity.shared::cta.b64 p, [%1], %2;\nselp.u32 %0, 1, 0, p;\n}" : "=r"(ok) : "r"(b), "r"(ph) : "memory");
        if (++it > SPIN_LIMIT) __trap();
    } while (!ok);
}
__device__ __forceinline__ bool mbar_test(uint32_t b, uint32_t ph) {
    uint32_t ok;
    asm volatile("{\n.reg .pred p;\nmbarrier.test_wait.parity.shared::cta.b64 p, [%1], %2;\nselp.u32 %0, 1, 0, p;\n}" : "=r"(ok) : "r"(b), "r"(ph) : "memory");
    return ok;
}
__device__ __forceinline__ void bulk(uint32_t dst, const void* src, uint32_t bytes, uint32_t bar, uint64_t pol) {
    asm volatile("cp.async.bulk.shared::cluster.global.mbarrier::complete_tx::bytes.L2::cache_hint [%0], [%1], %2, [%3], %4;" ::"r"(dst), "l"(src), "r"(bytes), "r"(bar), "l"(pol) : "memory");
}
__device__ __forceinline__ uint64_t evict_first() {
    uint64_t pol;
    asm volatile("createpolicy.fractional.L2::evict_first.b64 %0, 1.0;" : "=l"(pol));
    return pol;
}
__device__ __forceinline__ uint4 lds128(uint32_t a) {
    uint4 v;
    asm volatile("ld.shared.v4.u32 {%0,%1,%2,%3}, [%4];" : "=r"(v.x), "=r"(v.y), "=r"(v.z), "=r"(v.w) : "r"(a));
    return v;
}
__device__ __forceinline__ uint4 ldsm4t(uint32_t a) {
    uint4 v;
    asm volatile("ldmatrix.sync.aligned.m8n8.x4.trans.shared.b16 {%0,%1,%2,%3}, [%4];" : "=r"(v.x), "=r"(v.y), "=r"(v.z), "=r"(v.w) : "r"(a));
    return v;
}
__device__ __forceinline__ void mma(float (&c)[4], uint32_t a0, uint32_t a1, uint32_t a2, uint32_t a3, uint32_t b0, uint32_t b1) {
    asm volatile("mma.sync.aligned.m16n8k16.row.col.f32.bf16.bf16.f32 {%0,%1,%2,%3}, {%4,%5,%6,%7}, {%8,%9}, {%0,%1,%2,%3};"
                 : "+f"(c[0]), "+f"(c[1]), "+f"(c[2]), "+f"(c[3]) : "r"(a0), "r"(a1), "r"(a2), "r"(a3), "r"(b0), "r"(b1));
}
__device__ __forceinline__ void mma_top(float (&c)[4], uint32_t a0, uint32_t a2, uint32_t b0, uint32_t b1) {
    asm volatile("{\n.reg .b32 u1, u3;\nmma.sync.aligned.m16n8k16.row.col.f32.bf16.bf16.f32 {%0,%1,%2,%3}, {%4,u1,%5,u3}, {%6,%7}, {%0,%1,%2,%3};\n}"
                 : "+f"(c[0]), "+f"(c[1]), "+f"(c[2]), "+f"(c[3]) : "r"(a0), "r"(a2), "r"(b0), "r"(b1));
}
__device__ __forceinline__ void put_q(unsigned char* q, int i, uint4 v) {
    uint32_t* d = (uint32_t*)(q + (i >> 4) * 128 + (i & 1) * 64 + (i & 6) * 8 + (i & 8) / 2);
    d[0] = __byte_perm(v.x, v.y, 0x7632);
    d[2] = __byte_perm(v.z, v.w, 0x7632);
}
__device__ __forceinline__ uint4 ldg_nc(const void* p) {
    uint4 v;
    asm volatile("ld.global.nc.L1::no_allocate.v4.u32 {%0,%1,%2,%3}, [%4];" : "=r"(v.x), "=r"(v.y), "=r"(v.z), "=r"(v.w) : "l"(p));
    return v;
}
__device__ __forceinline__ uint4 ld_poll4(const void* p) {
    uint4 v;
    asm volatile("ld.relaxed.gpu.global.v4.u32 {%0,%1,%2,%3}, [%4];" : "=r"(v.x), "=r"(v.y), "=r"(v.z), "=r"(v.w) : "l"(p) : "memory");
    return v;
}
__device__ __forceinline__ uint2 ld_poll2(const void* p) {
    uint2 v;
    asm volatile("ld.relaxed.gpu.global.v2.u32 {%0,%1}, [%2];" : "=r"(v.x), "=r"(v.y) : "l"(p) : "memory");
    return v;
}
__device__ __forceinline__ void repoll4(uint4& v, const void* p, uint32_t tag) {
    const uint32_t bad = ((v.x ^ tag) | (v.y ^ tag) | (v.z ^ tag) | (v.w ^ tag)) & 15u;
    asm volatile("{\n.reg .pred p;\nsetp.ne.u32 p, %5, 0;\n@p ld.relaxed.gpu.global.v4.u32 {%0,%1,%2,%3}, [%4];\n}"
                 : "+r"(v.x), "+r"(v.y), "+r"(v.z), "+r"(v.w) : "l"(p), "r"(bad) : "memory");
}
__device__ __forceinline__ void repoll2(uint2& v, const void* p, uint32_t tag) {
    const uint32_t bad = ((v.x ^ tag) | (v.y ^ tag)) & 15u;
    asm volatile("{\n.reg .pred p;\nsetp.ne.u32 p, %3, 0;\n@p ld.relaxed.gpu.global.v2.u32 {%0,%1}, [%2];\n}"
                 : "+r"(v.x), "+r"(v.y) : "l"(p), "r"(bad) : "memory");
}
__device__ __forceinline__ uint32_t ld_poll1(const void* p) {
    uint32_t v;
    asm volatile("ld.relaxed.gpu.global.u32 %0, [%1];" : "=r"(v) : "l"(p) : "memory");
    return v;
}
__device__ __forceinline__ void st_pub4(void* p, uint32_t a, uint32_t b, uint32_t c, uint32_t d) {
    asm volatile("st.relaxed.gpu.global.v4.u32 [%0], {%1,%2,%3,%4};" ::"l"(p), "r"(a), "r"(b), "r"(c), "r"(d) : "memory");
}
__device__ __forceinline__ void st_pub2(void* p, uint32_t a, uint32_t b) {
    asm volatile("st.relaxed.gpu.global.v2.u32 [%0], {%1,%2};" ::"l"(p), "r"(a), "r"(b) : "memory");
}
__device__ __forceinline__ void st_pub1(void* p, uint32_t a) {
    asm volatile("st.relaxed.gpu.global.u32 [%0], %1;" ::"l"(p), "r"(a) : "memory");
}
__device__ __forceinline__ int ticket(unsigned* p) {
    int v;
    asm volatile("atom.relaxed.gpu.global.inc.u32 %0, [%1], %2;" : "=r"(v) : "l"(p), "n"(NDRAW - 1) : "memory");
    return v;
}
__device__ __forceinline__ uint32_t tg(float v, uint32_t tag) { return (__float_as_uint(v) & ~15u) | tag; }
__device__ __forceinline__ float blo(uint32_t v) { return __uint_as_float(v << 16); }
__device__ __forceinline__ float bhi(uint32_t v) { return __uint_as_float(v & 0xffff0000u); }
__device__ __forceinline__ float ex2(float x) { float r; asm("ex2.approx.ftz.f32 %0, %1;" : "=f"(r) : "f"(x)); return r; }
__device__ __forceinline__ uint32_t packbf(float lo, float hi) {
    uint32_t r;
    asm("cvt.rn.bf16x2.f32 %0, %1, %2;" : "=r"(r) : "f"(hi), "f"(lo));
    return r;
}
__device__ __forceinline__ void fma8(float (&a)[8], uint4 w, float x) {
    a[0] = fmaf(blo(w.x), x, a[0]); a[1] = fmaf(bhi(w.x), x, a[1]);
    a[2] = fmaf(blo(w.y), x, a[2]); a[3] = fmaf(bhi(w.y), x, a[3]);
    a[4] = fmaf(blo(w.z), x, a[4]); a[5] = fmaf(bhi(w.z), x, a[5]);
    a[6] = fmaf(blo(w.w), x, a[6]); a[7] = fmaf(bhi(w.w), x, a[7]);
}
__device__ __forceinline__ void spin(int cyc) { const uint32_t c0 = clock(); while ((uint32_t)clock() - c0 < (uint32_t)cyc) {} }
__device__ __forceinline__ void cbar() { asm volatile("bar.sync 1, 256;" ::: "memory"); }

__global__ void __launch_bounds__(NTHREADS, 1)
fused_decode_kernel(const __nv_bfloat16* __restrict__ x, const __nv_bfloat16* __restrict__ Kc, const __nv_bfloat16* __restrict__ Vc,
                    const __nv_bfloat16* __restrict__ wq, const __nv_bfloat16* __restrict__ wo,
                    const __nv_bfloat16* __restrict__ wg, const __nv_bfloat16* __restrict__ wu,
                    const __nv_bfloat16* __restrict__ wd, const __nv_bfloat16* __restrict__ gw,
                    __nv_bfloat16* __restrict__ out) {
    extern __shared__ __align__(1024) unsigned char smem[];
    const int tid = threadIdx.x, lane = tid & 31, warp = tid >> 5, cta = blockIdx.x;
    const uint32_t sb = s2u(smem);
    const uint32_t bFull = sb + OFF_BAR, bDone = bFull + NS * 8, bEmpty = bDone + NS * 8, bW = bEmpty + NS * 8,
                   bHfin = bW + 8, bNop = bW + 16, bCb = bW + 24, bOfin = bCb + 16, bQ = bOfin + 8;
    float* xs = (float*)(smem + OFF_X);
    volatile int2* meta = (volatile int2*)(smem + OFF_META);
    const int r0 = (cta * 43) >> 2, nr = (((cta + 1) * 43) >> 2) - r0;

    uint4 wreg[8];
    int pw;
    asm volatile("shr.u32 %0, %1, 5;" : "=r"(pw) : "r"(tid));
    if (pw == 8) {
        if (lane == 0) {
#pragma unroll
            for (int i = 0; i < 3 * NS + 7; i++) mbar_init(bFull + i * 8, (i == 3 * NS + 6 || i == 3 * NS + 1) ? 2 : 1);
            asm volatile("fence.mbarrier_init.release.cluster;" ::: "memory");
        }
        __syncwarp();
        asm volatile("bar.arrive 3, %0;" ::"n"(NTHREADS) : "memory");
    } else if (warp < 8) {
        if (cta < 128) {
            const __nv_bfloat16* p = wq + (size_t)(tid >> 2) * 8 * 4096 + cta * 32 + (tid & 3) * 8;
#pragma unroll
            for (int i = 0; i < 8; i++) wreg[i] = ldg_nc(p + (size_t)i * 4096);
        }
    } else if (pw >= 10) {
        wreg[0] = ldg_nc(x + (tid - 320) * 8);
        wreg[1].x = ld_poll1(&g_epoch);
    }
    if (warp != 8) asm volatile("bar.sync 3, %0;" ::"n"(NTHREADS) : "memory");

    if (warp == 8) {
        if (lane == 0) {
            const uint64_t pol = evict_first();
            int ta = cta - G * PSTAT, tb = ta + G, tc;
            int st = 0, cst = NS - CAP;
            uint32_t eph = 1, cph = 1;
            const __nv_bfloat16 *Kp = Kc + (size_t)G * PSTAT * 4096, *Vp = Vc + (size_t)G * PSTAT * 4096;
#define STEP(cur, nxt, nn)                                                                   \
            if (cur >= NUNITS - G * PSTAT) break;                                            \
            if (cur < -2 * G) nn = cur + 2 * G; else nn = ticket(&g_ctr);                    \
            if (cur < NUNITS - G * PSTAT - EAGER) mbar_wait(bFull + cst * 8, cph);           \
            mbar_wait(bEmpty + st * 8, eph);                                                 \
            mbar_expect_only(bFull + st * 8, 16384);                                         \
            bulk(sb + st * 16384, Kp + (ptrdiff_t)cur * 4096, 8192, bFull + st * 8, pol);    \
            bulk(sb + st * 16384 + 8192, Vp + (ptrdiff_t)cur * 4096, 8192, bFull + st * 8, pol); \
            meta[st].x = cur + G * PSTAT; meta[st].y = nxt + G * PSTAT;                      \
            mbar_arrive(bFull + st * 8);                                                     \
            if (++st == NS) { st = 0; eph ^= 1; }                                            \
            if (++cst == NS) { cst = 0; cph ^= 1; }
            while (true) {
                STEP(ta, tb, tc)
                STEP(tb, tc, ta)
                STEP(tc, ta, tb)
            }
#undef STEP
            const uint32_t tend = clock();
            *(volatile int*)(smem + OFF_N) = st;
            const int last = st == 0 ? NS - 1 : st - 1;
            const uint32_t lph = st == 0 ? eph : eph ^ 1;
            int wsl = st;
#pragma unroll 1
            for (int i = 0; i < 8; i++) {
                mbar_wait(bEmpty + st * 8, eph);
                meta[st].x = -1;
                mbar_arrive(bFull + st * 8);
                if (++st == NS) { st = 0; eph ^= 1; }
                if (i == 2 && cta < 128) {
                    mbar_expect(bW, nr * 1024 + 32768);
                    const __nv_bfloat16* src = wd + (size_t)r0 * 512;
                    uint32_t bytes = nr * 1024;
                    while (!mbar_test(bFull + last * 8, lph) && (uint32_t)clock() - tend < WTO) {}
#pragma unroll 1
                    for (int j = 0; j < 3; j++) {
                        bulk(sb + wsl * 16384, src, bytes, bW, pol);
                        src = wo + (size_t)(cta * 32 + j * 16) * 512;
                        bytes = 16384;
                        if (++wsl == NS) wsl = 0;
                    }
                }
            }
        }
    } else if (warp == 9) {
        const unsigned epoch = ld_poll1(&g_epoch);
        float m = -1e30f, l = 0.f, o0 = 0.f, o1 = 0.f, o2 = 0.f, o3 = 0.f;
        int st = 0; uint32_t ph = 0;
        const int myh = cta >> 2;
        uint4 cons = make_uint4(0u, 0u, 0u, 0u);
        bool live = false;
        while (true) {
            mbar_wait(live ? bDone + st * 8 : bOfin, live ? ph : 1u);
            const int u = live ? meta[st].x : 0, nx = live ? meta[st].y : 0;
            const float* res = (const float*)(smem + OFF_RES + st * 528);
            const float4 v = *(const float4*)(res + lane * 4);
            const float2 ml = *(const float2*)(res + 128);
            __syncwarp();
            if (lane == 0) mbar_arrive(live ? bEmpty + st * 8 : bNop);
            const float mn = fmaxf(m, ml.x);
            const float a = ex2(m - mn), b = ex2(ml.x - mn);
            m = mn;
            l = l * a + ml.y * b;
            o0 = o0 * a + v.x * b; o1 = o1 * a + v.y * b; o2 = o2 * a + v.z * b; o3 = o3 * a + v.w * b;
            const int nb = min(nx >> 9, 64);
            for (int bh = u >> 9; bh < nb; bh++) {
                const uint32_t ptag = PTAG(bh);
                if (bh >= RING) {
                    int it = 0;
                    while (cons.x != epoch + 1 || cons.y != epoch + 1 || cons.z != epoch + 1 || cons.w != epoch + 1) {
                        cons = ld_poll4(&g_cons[bh - RING]);
                        if (++it > SPIN_LIMIT) __trap();
                    }
                }
                if (bh == YCLR && cta < 128) {
#pragma unroll
                    for (int i = 0; i < 8; i++) st_pub4(&g_y[cta * 256 + i * 32 + lane], 0u, 0u, 0u, 0u);
                    __threadfence();
                    __syncwarp();
                }
                st_pub4(&g_po[(((bh % RING) * 4 + (lane >> 3)) * G + cta) * 8 + (lane & 7)], tg(o0, ptag), tg(o1, ptag), tg(o2, ptag), tg(o3, ptag));
                if (lane == 0) {
                    st_pub2(&g_pml[(bh % RING) * G + cta], tg(m, ptag), tg(l, ptag));
                    if ((bh & 31) == myh) mbar_arrive(bCb + (bh >> 5) * 8);
                }
                if (bh + 1 >= RING && bh < 63) cons = ld_poll4(&g_cons[bh + 1 - RING]);
                m = -1e30f; l = 0.f; o0 = o1 = o2 = o3 = 0.f;
            }
            if (nb == 64) { if (lane == 0) mbar_arrive(bHfin); break; }
            if (!live) { live = true; m = -1e30f; l = 0.f; o0 = o1 = o2 = o3 = 0.f; continue; }
            if (++st == NS) { st = 0; ph ^= 1; }
        }
    } else if (warp >= 10) {
        const int cw = warp - 10;
        const uint4 xr0 = wreg[0];
        const unsigned epoch = wreg[1].x;
        const uint32_t tag = epoch % 15u + 1u;
        {
            if (tid == 320) *(volatile uint32_t*)(smem + OFF_N + 4) = tag;
            float4* d = (float4*)(xs + (tid - 320) * 8);
            d[0] = make_float4(blo(xr0.x), bhi(xr0.x), blo(xr0.y), bhi(xr0.y));
            d[1] = make_float4(blo(xr0.z), bhi(xr0.z), blo(xr0.w), bhi(xr0.w));
            asm volatile("bar.arrive 4, 384;" ::: "memory");
            asm volatile("bar.sync 2, 128;" ::: "memory");
        }
        if (cw >= 2) {
            asm volatile("bar.sync 5, 320;" ::: "memory");
#pragma unroll 1
            for (int j = 0; j < 4; j++) {
                uint4 v[7];
                const int i0 = 256 + j * 448 + tid - 384;
                int it = 0;
                while (true) {
                    uint32_t bad = 0;
#pragma unroll
                    for (int i = 0; i < 7; i++) v[i] = ld_poll4((const uint4*)g_q + i0 + i * 64);
#pragma unroll
                    for (int i = 0; i < 7; i++) bad |= (v[i].x ^ tag) | (v[i].y ^ tag) | (v[i].z ^ tag) | (v[i].w ^ tag);
                    if ((bad & 0xffffu) == 0) break;
                    if (++it > SPIN_LIMIT) __trap();
                    __nanosleep(200);
                }
#pragma unroll
                for (int i = 0; i < 7; i++)
                    put_q(smem + OFF_Q, i0 + i * 64, v[i]);
            }
            __syncwarp();
            if (lane == 0) mbar_arrive(bQ);
        }
        if (cta >= G - 11) {
            const int f0 = min((cta - (G - 11)) * 128 + (lane & 15) * 8, DF - 8), b = lane >> 4;
            float ag[2][8], au[2][8];
#pragma unroll
            for (int i = 0; i < 8; i++) ag[0][i] = ag[1][i] = au[0][i] = au[1][i] = 0.f;
            const size_t off = (size_t)(cw * 128 + b) * DF + f0;
#pragma unroll 1
            for (int it = 0; it < 8; it++) {
                uint4 wa[8], wb[8];
#pragma unroll
                for (int i = 0; i < 8; i++) {
                    wa[i] = ldg_nc(wg + off + (size_t)(it * 16 + i * 2) * DF);
                    wb[i] = ldg_nc(wu + off + (size_t)(it * 16 + i * 2) * DF);
                }
#pragma unroll
                for (int i = 0; i < 8; i++) {
                    const int r = cw * 128 + it * 16 + i * 2 + b;
                    const float x0 = xs[r], x1 = xs[512 + r];
                    fma8(ag[0], wa[i], x0); fma8(ag[1], wa[i], x1);
                    fma8(au[0], wb[i], x0); fma8(au[1], wb[i], x1);
                }
            }
            float gv[8], uv[8];
#pragma unroll
            for (int i = 0; i < 8; i++) {
                gv[i] = (b ? ag[1][i] : ag[0][i]) + __shfl_xor_sync(~0u, b ? ag[0][i] : ag[1][i], 16);
                uv[i] = (b ? au[1][i] : au[0][i]) + __shfl_xor_sync(~0u, b ? au[0][i] : au[1][i], 16);
            }
            float* acc = (float*)(smem + OFF_RED) + lane;
#pragma unroll 1
            for (int k = 0; k < 4; k++) {
                if (((cw + 2) & 3) == k) {
#pragma unroll
                    for (int i = 0; i < 8; i++) {
                        if (k > 0) { gv[i] += acc[i * 64]; uv[i] += acc[i * 64 + 32]; }
                        acc[i * 64] = gv[i]; acc[i * 64 + 32] = uv[i];
                    }
                }
                asm volatile("bar.sync 2, 128;" ::: "memory");
            }
            if (cw == 1) {
                uint32_t hv[8];
#pragma unroll
                for (int i = 0; i < 8; i++) {
                    const float t = tanhf(0.7978845608028654f * (gv[i] + 0.044715f * gv[i] * gv[i] * gv[i]));
                    hv[i] = tg(0.5f * gv[i] * (1.f + t) * uv[i], tag);
                }
                uint32_t* d = &g_h[b * DF + f0];
                st_pub4(d, hv[0], hv[1], hv[2], hv[3]);
                st_pub4(d + 4, hv[4], hv[5], hv[6], hv[7]);
            }
        }
        if (cta < 128) {
            __nv_bfloat16* coef = (__nv_bfloat16*)(smem + OFF_COEF);
            float* cmb = (float*)(smem + OFF_CMB);
            float gate0 = 0.f, gate1 = 0.f;
            if (cw == 0) {
                const uint4 w0 = ldg_nc(gw + lane * 16), w1 = ldg_nc(gw + lane * 16 + 8);
                const uint32_t w[8] = {w0.x, w0.y, w0.z, w0.w, w1.x, w1.y, w1.z, w1.w};
#pragma unroll
                for (int i = 0; i < 8; i++) {
                    gate0 = fmaf(blo(w[i]), xs[lane * 16 + 2 * i], gate0);
                    gate0 = fmaf(bhi(w[i]), xs[lane * 16 + 2 * i + 1], gate0);
                    gate1 = fmaf(blo(w[i]), xs[512 + lane * 16 + 2 * i], gate1);
                    gate1 = fmaf(bhi(w[i]), xs[512 + lane * 16 + 2 * i + 1], gate1);
                }
#pragma unroll
                for (int k = 1; k < 32; k <<= 1) {
                    gate0 += __shfl_xor_sync(~0u, gate0, k);
                    gate1 += __shfl_xor_sync(~0u, gate1, k);
                }
                gate0 = 1.f / (1.f + __expf(-gate0));
                gate1 = 1.f / (1.f + __expf(-gate1));
            }
#pragma unroll 1
            for (int b = 0; b < 2; b++) {
                const int bh = b * 32 + (cta >> 2);
                if (b == 1 && cw == 0) {
                    const int r = lane & 15, bb = lane >> 4;
                    uint32_t hv = tag;
                    if (r < nr) {
                        int it = 0;
                        do {
                            hv = ld_poll1(&g_h[bb * DF + r0 + r]);
                            if (++it > SPIN_LIMIT) __trap();
                            if ((hv & 15u) != tag) __nanosleep(1000);
                        } while ((hv & 15u) != tag);
                    }
                    coef[bb * 48 + r] = __float2bfloat16(r < nr ? __uint_as_float(hv) * (1.f - (bb ? gate1 : gate0)) : 0.f);
                    __syncwarp();
                    if (lane == 0) mbar_arrive(bHfin);
                }
                mbar_wait(bCb + b * 8, 0);
                const uint4* po = &g_po[((bh % RING) * 4 + (cta & 3)) * G * 8];
                const uint2* pm = &g_pml[(bh % RING) * G];
                const uint32_t ptag = PTAG(bh);
                uint4 v[9];
                uint2 ml = make_uint2(0u, 0u), mle = ml;
#pragma unroll
                for (int i = 0; i < 9; i++) v[i] = make_uint4(0u, 0u, 0u, 0u);
                int it = 0;
                while (true) {
                    repoll2(ml, pm + cw * 32 + lane, ptag);
                    repoll2(mle, pm + 128 + cw, ptag);
#pragma unroll
                    for (int i = 0; i < 8; i++) repoll4(v[i], po + cw * 256 + i * 32 + lane, ptag);
                    repoll4(v[8], po + (128 + cw) * 8 + (lane & 7), ptag);
                    uint32_t bad = (v[8].x ^ ptag) | (v[8].y ^ ptag) | (v[8].z ^ ptag) | (v[8].w ^ ptag);
#pragma unroll
                    for (int i = 7; i >= 0; i--) bad |= (v[i].x ^ ptag) | (v[i].y ^ ptag) | (v[i].z ^ ptag) | (v[i].w ^ ptag);
                    bad |= (ml.x ^ ptag) | (ml.y ^ ptag) | (mle.x ^ ptag) | (mle.y ^ ptag);
                    const bool ok = !__any_sync(~0u, (bad & 15u) != 0);
                    if (ok) {
                        int key = __float_as_int(fmaxf(__uint_as_float(ml.x), __uint_as_float(mle.x)));
                        key = __reduce_max_sync(~0u, key ^ ((key >> 31) & 0x7fffffff));
                        const float M = __int_as_float(key ^ ((key >> 31) & 0x7fffffff));
                        const float w = ex2(__uint_as_float(ml.x) - M), wl = w * __uint_as_float(ml.y & ~15u);
                        const float we = lane < 8 ? ex2(__uint_as_float(mle.x) - M) : 0.f;
                        float L = we * __uint_as_float(mle.y & ~15u);
                        float o0 = we * __uint_as_float(v[8].x), o1 = we * __uint_as_float(v[8].y), o2 = we * __uint_as_float(v[8].z), o3 = we * __uint_as_float(v[8].w);
#pragma unroll
                        for (int i = 0; i < 8; i++) {
                            const float wi = __shfl_sync(~0u, w, 4 * i + (lane >> 3));
                            L += __shfl_sync(~0u, wl, 4 * i + (lane >> 3));
                            o0 = fmaf(wi, __uint_as_float(v[i].x), o0); o1 = fmaf(wi, __uint_as_float(v[i].y), o1);
                            o2 = fmaf(wi, __uint_as_float(v[i].z), o2); o3 = fmaf(wi, __uint_as_float(v[i].w), o3);
                        }
#pragma unroll
                        for (int k = 8; k < 32; k <<= 1) {
                            o0 += __shfl_xor_sync(~0u, o0, k); o1 += __shfl_xor_sync(~0u, o1, k);
                            o2 += __shfl_xor_sync(~0u, o2, k); o3 += __shfl_xor_sync(~0u, o3, k);
                            L += __shfl_xor_sync(~0u, L, k);
                        }
                        if (lane < 8) *(float4*)(cmb + cw * 36 + lane * 4) = make_float4(o0, o1, o2, o3);
                        if (lane == 8) *(float2*)(cmb + cw * 36 + 32) = make_float2(M, L);
                    }
                    if (ok) break;
                    if (++it > SPIN_LIMIT) __trap();
                }
                __syncwarp();
                asm volatile("bar.sync 2, 128;" ::: "memory");
                if (cw == 0) {
                    {
                        const float2 a0 = *(const float2*)(cmb + 32), a1 = *(const float2*)(cmb + 68), a2 = *(const float2*)(cmb + 104), a3 = *(const float2*)(cmb + 140);
                        const float MM = fmaxf(fmaxf(a0.x, a1.x), fmaxf(a2.x, a3.x));
                        const float e0 = ex2(a0.x - MM), e1 = ex2(a1.x - MM), e2 = ex2(a2.x - MM), e3 = ex2(a3.x - MM);
                        const float LL = (e0 * a0.y + e1 * a1.y) + (e2 * a2.y + e3 * a3.y);
                        const float o = (e0 * cmb[lane] + e1 * cmb[36 + lane]) + (e2 * cmb[72 + lane] + e3 * cmb[108 + lane]);
                        coef[b * 48 + 16 + lane] = __float2bfloat16(o * __fdividef(b ? gate1 : gate0, LL));
                        __syncwarp();
                        if (b == 1 && lane == 0) mbar_arrive(bOfin);
                    }
                    if (lane == 0) st_pub1((uint32_t*)&g_cons[bh] + (cta & 3), epoch + 1);
                    if (lane == 0 && b == 1 && cta == 127) g_epoch = epoch + 1;
                }
                if (b == 0) asm volatile("bar.sync 2, 128;" ::: "memory");
            }
        }
    } else {
        float* red = (float*)(smem + OFF_RED);
        const int g = lane >> 2, t = lane & 3;
        const uint32_t kE = g * 256 + t * 16 + (g & 1) * 64, kO = g * 256 + t * 16 + 64 - (g & 1) * 64;
        uint32_t voff[8], msk[8];
        {
            const int mi = lane >> 3, i = lane & 7;
            const uint32_t vb = 8192 + (8 * (mi & 1) + i) * 256 + 128 * (mi >> 1);
#pragma unroll
            for (int c = 0; c < 8; c++) {
                voff[c] = vb + ((c + i) & 7) * 16;
                msk[c] = (((c + 2 * t) & 7) == g ? 0x0000ffffu : 0u) | (((c + 2 * t + 1) & 7) == g ? 0xffff0000u : 0u);
            }
        }
        const float SC = 0.08838834764831845f * 1.4426950408889634f;
        int st = warp, qlim = 8 * 512; uint32_t ph = 0;
#pragma unroll 1
        for (int pass = 0; pass < 2; pass++) {
        if (pass) {
        asm volatile("bar.sync 4, 384;" ::: "memory");
        const uint32_t tag = *(volatile uint32_t*)(smem + OFF_N + 4);
        if (cta < 128) {
            float a0[8], a1[8];
#pragma unroll
            for (int i = 0; i < 8; i++) a0[i] = a1[i] = 0.f;
#pragma unroll
            for (int i = 0; i < 8; i++) {
                asm volatile("" : "+r"(wreg[i].x), "+r"(wreg[i].y), "+r"(wreg[i].z), "+r"(wreg[i].w));
                fma8(a0, wreg[i], xs[(tid >> 2) * 8 + i]);
                fma8(a1, wreg[i], xs[512 + (tid >> 2) * 8 + i]);
            }
#pragma unroll
            for (int i = 0; i < 8; i++)
#pragma unroll
                for (int s = 4; s < 32; s <<= 1) {
                    a0[i] += __shfl_xor_sync(~0u, a0[i], s);
                    a1[i] += __shfl_xor_sync(~0u, a1[i], s);
                }
            if (lane < 8) {
                float4* d = (float4*)(red + warp * 64 + lane * 8);
                if (lane < 4) { d[0] = make_float4(a0[0], a0[1], a0[2], a0[3]); d[1] = make_float4(a0[4], a0[5], a0[6], a0[7]); }
                else          { d[0] = make_float4(a1[0], a1[1], a1[2], a1[3]); d[1] = make_float4(a1[4], a1[5], a1[6], a1[7]); }
            }
            cbar();
            if (tid < 64) {
                float s = 0.f;
#pragma unroll
                for (int w = 0; w < 8; w++) s += red[w * 64 + tid];
                st_pub1(&g_q[(tid >> 5) * 4096 + cta * 32 + (tid & 31)], (packbf(0.f, s) & 0xffff0000u) | tag);
            }
        }
            uint4 v;
            int it = 0;
            do {
                v = ld_poll4((const uint4*)g_q + tid);
                if (++it > SPIN_LIMIT) __trap();
            } while ((((v.x ^ tag) | (v.y ^ tag) | (v.z ^ tag) | (v.w ^ tag)) & 0xffffu) != 0);
            put_q(smem + OFF_Q, tid, v);
            asm volatile("bar.sync 5, 320;" ::: "memory");
        }

        while (true) {
            mbar_wait(bDone + st * 8, ph ^ 1);
            mbar_wait((pass ? bFull : bDone) + st * 8, pass ? ph : 1u);
            const int u = pass ? meta[st].x : 0;
            if (u < 0) break;
            if (u >= qlim) { mbar_wait(bQ, 0); qlim = NUNITS; }
            const uint32_t base = sb + st * 16384;
            const uint32_t qa = sb + OFF_Q + (u >> 9) * 256 + t * 16;
            uint4 Q[4];
#pragma unroll
            for (int j = 0; j < 4; j++) Q[j] = lds128(qa + j * 64);
            float s[2][4][4];
#pragma unroll
            for (int n = 0; n < 8; n++) s[n >> 2][n & 3][0] = s[n >> 2][n & 3][1] = s[n >> 2][n & 3][2] = s[n >> 2][n & 3][3] = 0.f;
#pragma unroll
            for (int j = 0; j < 4; j++) {
#pragma unroll
                for (int n = 0; n < 4; n++) {
                    const uint4 kk = lds128(base + n * 2048 + ((j & 1) ? kO : kE) + (j >> 1) * 128);
                    mma(s[j & 1][n], Q[j & 2].x, Q[j & 2].y, Q[j & 2].z, Q[j & 2].w, kk.x, kk.y);
                    mma(s[j & 1][n], Q[j | 1].x, Q[j | 1].y, Q[j | 1].z, Q[j | 1].w, kk.z, kk.w);
                }
            }
            float sa[4], sc[4];
#pragma unroll
            for (int n = 0; n < 4; n++) { sa[n] = s[0][n][0] + s[1][n][2]; sc[n] = s[0][n][3] + s[1][n][1]; }
            float mx = fmaxf(fmaxf(fmaxf(sa[0], sc[0]), fmaxf(sa[1], sc[1])), fmaxf(fmaxf(sa[2], sc[2]), fmaxf(sa[3], sc[3])));
            mx = fmaxf(mx, __shfl_xor_sync(~0u, mx, 1));
            mx = fmaxf(mx, __shfl_xor_sync(~0u, mx, 2));
            const float mu = mx * SC;
            uint32_t P[4];
            float l = 0.f;
#pragma unroll
            for (int n = 0; n < 4; n++) {
                const float p0 = ex2(fmaf(sa[n], SC, -mu)), p1 = ex2(fmaf(sc[n], SC, -mu));
                l += p0 + p1;
                P[n] = packbf(p0, p1);
            }
            l += __shfl_xor_sync(~0u, l, 1);
            l += __shfl_xor_sync(~0u, l, 2);
            float o[4][4];
#pragma unroll
            for (int n = 0; n < 4; n++) o[n][0] = o[n][1] = o[n][2] = o[n][3] = 0.f;
#pragma unroll
            for (int c = 0; c < 8; c++) {
#pragma unroll
                for (int T = 0; T < 2; T++) {
                    const uint4 vv = ldsm4t(base + voff[c] + T * 4096);
                    const uint32_t pl = P[2 * T] & msk[c], phh = P[2 * T + 1] & msk[c];
                    mma_top(o[2 * T], pl, phh, vv.x, vv.y);
                    mma_top(o[2 * T + 1], pl, phh, vv.z, vv.w);
                }
            }
            float* res = (float*)(smem + OFF_RES + st * 528);
            *(float2*)(res + 2 * lane) = make_float2(o[0][0] + o[2][0], o[0][1] + o[2][1]);
            *(float2*)(res + 64 + 2 * lane) = make_float2(o[1][0] + o[3][0], o[1][1] + o[3][1]);
            if (lane == 0) *(float2*)(res + 128) = make_float2(mu, l);
            __syncwarp();
            if (lane == 0) mbar_arrive(pass ? bDone + st * 8 : bNop);
            if (!pass) break;
            st += 8;
            if (st >= NS) { st -= NS; ph ^= 1; }
        }
        }
#pragma unroll 1
        for (int pass = mbar_test(bW, 0) ? 1 : 0; pass < 2; pass++) {
        if (cta < 128) {
            const int s0 = pass ? *(volatile int*)(smem + OFF_N) : 0;
            const uint32_t* coef = (const uint32_t*)(smem + OFF_COEF);
            float y[4][4];
#pragma unroll
            for (int i = 0; i < 4; i++) y[i][0] = y[i][1] = y[i][2] = y[i][3] = 0.f;
            const int mi = lane >> 3, wrow = 8 * (mi & 1) + (lane & 7);
            if (pass) { mbar_wait(bW, 0); mbar_wait(bHfin, 0); }
            uint4 vv[3][4];
#pragma unroll
            for (int i = 0; i < 3; i++) {
                int sl = s0 + i; if (sl >= NS) sl -= NS;
                const uint32_t wb = (pass ? sb + sl * 16384 + (i == 0 ? min(wrow, nr - 1) : wrow) * 1024 : sb + OFF_Q) + warp * 128;
#pragma unroll
                for (int c = 0; c < 4; c++) vv[i][c] = ldsm4t(wb + ((2 * c + (mi >> 1) + lane) & 7) * 16);
            }
            uint32_t cf[3][4];
#pragma unroll
            for (int i = 0; i < 3; i++) { cf[i][0] = coef[i * 8 + t]; cf[i][2] = coef[i * 8 + 4 + t]; }
            cf[0][1] = coef[24 + t]; cf[0][3] = coef[28 + t];
#pragma unroll
            for (int i = 0; i < 3; i++) {
                if (i == 1) {
                    if (pass) mbar_wait(bOfin, 0);
                    cf[1][1] = coef[32 + t]; cf[1][3] = coef[36 + t]; cf[2][1] = coef[40 + t]; cf[2][3] = coef[44 + t];
                }
#pragma unroll
                for (int c = 0; c < 8; c += 2) {
                    mma(y[c & 2], cf[i][0] & msk[c], cf[i][1] & msk[c], cf[i][2] & msk[c], cf[i][3] & msk[c], vv[i][c >> 1].x, vv[i][c >> 1].y);
                    mma(y[(c & 2) + 1], cf[i][0] & msk[c + 1], cf[i][1] & msk[c + 1], cf[i][2] & msk[c + 1], cf[i][3] & msk[c + 1], vv[i][c >> 1].z, vv[i][c >> 1].w);
                }
            }
            uint2* yp = (uint2*)g_y;
            uint4 v;
            if (pass) {
                st_pub2(yp + (((64 + (tid >> 2)) * 128 + cta) * 4 + (tid & 3)), tg((y[0][2] + y[1][2]) + (y[2][2] + y[3][2]), YTAG), tg((y[0][3] + y[1][3]) + (y[2][3] + y[3][3]), YTAG));
                st_pub2(yp + (((tid >> 2) * 128 + cta) * 4 + (tid & 3)), tg((y[0][0] + y[1][0]) + (y[2][0] + y[3][0]), YTAG), tg((y[0][1] + y[1][1]) + (y[2][1] + y[3][1]), YTAG));
            }
            int it = 0;
            {
                const uint4* src = &g_y[cta * 256 + tid];
#define YOK(q) __all_sync(~0u, (((q.x & q.y) & (q.z & q.w)) & YTAG) != 0)
                uint4 p0 = make_uint4(YTAG, YTAG, YTAG, YTAG), p1 = p0, p2 = p0;
                if (pass) {
                    p0 = ld_poll4(src);
                    spin(STAG);
                    p1 = ld_poll4(src);
                    spin(STAG);
                }
                while (true) {
                    if (pass) p2 = ld_poll4(src);
                    if (YOK(p0)) { v = p0; break; }
                    p0 = ld_poll4(src);
                    if (YOK(p1)) { v = p1; break; }
                    p1 = ld_poll4(src);
                    if (YOK(p2)) { v = p2; break; }
                    if (++it > SPIN_LIMIT) __trap();
                }
#undef YOK
            }
            float f0 = __uint_as_float(v.x), f1 = __uint_as_float(v.y), f2 = __uint_as_float(v.z), f3 = __uint_as_float(v.w);
            {
                const bool hi = lane & 2;
                const float s0_ = hi ? f0 : f2, s1_ = hi ? f1 : f3;
                f0 = (hi ? f2 : f0) + __shfl_xor_sync(~0u, s0_, 2);
                f1 = (hi ? f3 : f1) + __shfl_xor_sync(~0u, s1_, 2);
                const bool h2 = lane & 4;
                f0 = (h2 ? f1 : f0) + __shfl_xor_sync(~0u, h2 ? f0 : f1, 4);
                f0 += __shfl_xor_sync(~0u, f0, 8);
                f0 += __shfl_xor_sync(~0u, f0, 16);
            }
            if (lane < 8 && pass) red[warp * 8 + (lane & 1) * 4 + (lane & 2) + (lane >> 2)] = f0;
            if (pass) cbar();
            if (tid < 8) {
                float s = 0.f;
#pragma unroll
                for (int w = 0; w < 8; w++) s += red[w * 8 + tid];
                if (pass) out[cta * 8 + tid] = __float2bfloat16(s);
            }
        }
        }
    }
}

extern "C" void kernel_launch(void* const* d_in, const int* in_sizes, int n_in, void* d_out, int out_size) {
    (void)in_sizes; (void)n_in; (void)out_size;
    cudaFuncSetAttribute(fused_decode_kernel, cudaFuncAttributeMaxDynamicSharedMemorySize, SMEM_BYTES);
    fused_decode_kernel<<<G, NTHREADS, SMEM_BYTES, cudaStreamPerThread>>>(
        (const __nv_bfloat16*)d_in[0], (const __nv_bfloat16*)d_in[1], (const __nv_bfloat16*)d_in[2],
        (const __nv_bfloat16*)d_in[3], (const __nv_bfloat16*)d_in[4], (const __nv_bfloat16*)d_in[6],
        (const __nv_bfloat16*)d_in[7], (const __nv_bfloat16*)d_in[8], (const __nv_bfloat16*)d_in[9],
        (__nv_bfloat16*)d_out);
}
```
